```python
import torch

def _softmax(x, axis=-1):
    return torch.softmax(x, dim=axis)

def _gelu(x):
    return torch.nn.functional.gelu(x, approximate='tanh')

def _silu(x):
    return torch.nn.functional.silu(x)

def _sigmoid(x):
    return torch.sigmoid(x)

def _layernorm(x, axis=-1, eps=1e-05):
    m = x.mean(dim=axis, keepdim=True)
    v = x.var(dim=axis, keepdim=True, unbiased=False)
    return (x - m) / torch.sqrt(v + eps)

def _scatter_add(tgt, idx, src, axis=0):
    return tgt.clone().index_add_(axis, idx, src)

def _segment_sum(src, seg, n):
    out = torch.zeros((n,) + src.shape[1:], dtype=src.dtype)
    return out.index_add_(0, seg, src)

def _pad(x, pw):
    flat = tuple((v for pair in reversed(pw) for v in pair))
    return torch.nn.functional.pad(x, flat)
kernel_name = 'adaLN_cond__memory_aug_recurrent_mem_tr__mixer_s_mlp__prompt'

def setup_inputs():

    _w = lambda a: (lambda t: t.to(torch.bfloat16) if t.is_floating_point() else t)(torch.as_tensor(a))

    def _A_setup():
        B, S, Dm = (1, 2048, 512)
        H, Dh = (32, 128)
        M, seg = (8, 32)
        seg = min(seg, S)
        S = S // seg * seg
        return {'x': _w((lambda *s: torch.randn(*s, dtype=torch.bfloat16) * 0.05)(B, S, Dm)), 'mem0': _w((lambda *s: torch.randn(*s, dtype=torch.bfloat16) * 0.4)(B, M, Dm)), 'Wq': _w((lambda *s: torch.randn(*s, dtype=torch.bfloat16) * 3.2)(Dm, H, Dh) * Dm ** (-0.5)), 'Wk': _w((lambda *s: torch.randn(*s, dtype=torch.bfloat16) * 3.2)(Dm, H, Dh) * Dm ** (-0.5)), 'Wv': _w((lambda *s: torch.randn(*s, dtype=torch.bfloat16) * 0.4)(Dm, H, Dh) * Dm ** (-0.5)), 'Wo': _w((lambda *s: torch.randn(*s, dtype=torch.bfloat16) * 0.4)(H, Dh, Dm) * (H * Dh) ** (-0.5)), 'seg_len': seg}
    _A_in = _A_setup()

    def _B_setup():
        B, S, D, F = (1, 2048, 512, 1376)
        return {'x': _w((lambda *s: torch.randn(*s, dtype=torch.bfloat16) * 0.05)(B, S, D)), 'w1': _w((lambda *s: torch.randn(*s, dtype=torch.bfloat16) * 3.2)(D, D) * D ** (-0.5)), 'w2': _w((lambda *s: torch.randn(*s, dtype=torch.bfloat16) * 3.2)(D, D) * D ** (-0.5)), 'w3': _w((lambda *s: torch.randn(*s, dtype=torch.bfloat16) * 3.2)(D, F) * D ** (-0.5)), 'w4': _w((lambda *s: torch.randn(*s, dtype=torch.bfloat16) * 3.2)(F, D) * F ** (-0.5))}
    _B_in = _B_setup()
    return {'A_x': _A_in['x'], 'A_mem0': _A_in['mem0'], 'A_Wq': _A_in['Wq'], 'A_Wk': _A_in['Wk'], 'A_Wv': _A_in['Wv'], 'A_Wo': _A_in['Wo'], 'A_seg_len': _A_in['seg_len'], 'B_x': _B_in['x'], 'B_w1': _B_in['w1'], 'B_w2': _B_in['w2'], 'B_w3': _B_in['w3'], 'B_w4': _B_in['w4'], 'c': _w((lambda *s: torch.randn(*s, dtype=torch.bfloat16) * 0.1)(1, 512) * 8.0), 'w_mod': _w((lambda *s: torch.randn(*s, dtype=torch.bfloat16) * 0.1)(512, 6 * 512) * 512 ** (-0.5) * 8.0)}

def reference(A_x, A_mem0, A_Wq, A_Wk, A_Wv, A_Wo, A_seg_len, B_x, B_w1, B_w2, B_w3, B_w4, c, w_mod):

    def _A_ref(x, mem0, Wq, Wk, Wv, Wo, seg_len):
        B, S, Dm = x.shape
        H, Dh = (Wq.shape[1], Wq.shape[2])
        M = mem0.shape[1]
        scale = Dh ** (-0.5)
        n_seg = S // seg_len
        L = M + seg_len
        idx = torch.arange(L)
        mask = (idx[:, None] < M) | (idx[:, None] >= idx[None, :])
        mem = mem0
        outs = []
        for s in range(n_seg):
            xs = x[:, s * seg_len:(s + 1) * seg_len, :].clone()
            h = torch.concatenate([mem, xs], axis=1)
            q = torch.einsum('btd,dhe->bhte', h, Wq)
            k = torch.einsum('btd,dhe->bhte', h, Wk)
            v = torch.einsum('btd,dhe->bhte', h, Wv)
            scores = torch.einsum('bhqe,bhke->bhqk', q, k) * scale
            scores = torch.where(mask[None, None], scores, -1000000000.0)
            p = _softmax(scores, axis=-1)
            o = torch.einsum('bhqk,bhke->bhqe', p, v)
            o = torch.einsum('bhte,hed->btd', o, Wo)
            mem = o[:, :M, :].clone()
            outs.append(o[:, M:, :])
        return torch.concatenate(outs, axis=1)

    def _B_ref(x, w1, w2, w3, w4):
        B, S, D = x.shape
        h = _gelu(_layernorm(x, axis=-1) @ w1)
        c = D // 4
        g0 = _pad(h[:, :, 0 * c:1 * c], ((0, 0), (1, 0), (0, 0)))[:, :S, :]
        g1 = _pad(h[:, :, 1 * c:2 * c], ((0, 0), (0, 1), (0, 0)))[:, 1:, :]
        g2 = _pad(h[:, :, 2 * c:3 * c], ((0, 0), (2, 0), (0, 0)))[:, :S, :]
        g3 = _pad(h[:, :, 3 * c:], ((0, 0), (0, 2), (0, 0)))[:, 2:, :]
        hs = torch.concatenate([g0, g1, g2, g3], axis=-1) @ w2
        x1 = x + hs
        h2 = _gelu(_layernorm(x1, axis=-1) @ w3) @ w4
        return x1 + h2
    x = A_x
    mod = (_silu(c) @ w_mod).reshape(c.shape[0], 6, 1, -1)
    sa, ca, ga, sb, cb, gb = (mod[:, 0].clone(), mod[:, 1].clone(), mod[:, 2].clone(), mod[:, 3].clone(), mod[:, 4].clone(), mod[:, 5].clone())
    h = _layernorm(x, axis=-1) * (1 + ca) + sa
    x = x + ga * _A_ref(h, A_mem0, A_Wq, A_Wk, A_Wv, A_Wo, A_seg_len)
    h = _layernorm(x, axis=-1) * (1 + cb) + sb
    x = x + gb * _B_ref(h, B_w1, B_w2, B_w3, B_w4)
    return x
```

```cpp
#include <cuda_runtime.h>
#include <cuda_bf16.h>
#include <stdint.h>

typedef __nv_bfloat16 bf16;

#define S_LEN 2048
#define DM    512
#define NH    32
#define DH    128
#define HD    (NH*DH)
#define MEMN  8
#define SEG   32
#define NSEG  (S_LEN/SEG)
#define FF    1376

__device__ float              g_mod[6*DM];
__device__ bf16               g_h1[S_LEN*DM];
__device__ bf16               g_qkv[(size_t)S_LEN*3*HD];
__device__ bf16               g_km[NSEG*MEMN*HD];
__device__ bf16               g_vm[NSEG*MEMN*HD];
__device__ unsigned long long g_acc[NSEG*MEMN*DM];
__device__ bf16               g_o[(size_t)S_LEN*HD];
__device__ bf16               g_x2[S_LEN*DM];
__device__ bf16               g_h2[S_LEN*DM];
__device__ bf16               g_a1[S_LEN*DM];
__device__ bf16               g_g[S_LEN*DM];
__device__ bf16               g_x1[S_LEN*DM];
__device__ bf16               g_a3[S_LEN*DM];
__device__ bf16               g_u[S_LEN*FF];

__device__ __forceinline__ float bfr(float x) { return __bfloat162float(__float2bfloat16_rn(x)); }
__device__ __forceinline__ uint32_t pack_bf16(float lo, float hi) {
    __nv_bfloat162 v = __floats2bfloat162_rn(lo, hi);
    return *reinterpret_cast<uint32_t*>(&v);
}
__device__ __forceinline__ float2 unpack_bf16(uint32_t u) {
    __nv_bfloat162 v = *reinterpret_cast<__nv_bfloat162*>(&u);
    return make_float2(__bfloat162float(v.x), __bfloat162float(v.y));
}
__device__ __forceinline__ uint32_t smem_u32(const void* p) { return (uint32_t)__cvta_generic_to_shared(p); }

__device__ __forceinline__ void mma16816(float* c, const uint32_t* a, const uint32_t* b) {
    asm volatile("mma.sync.aligned.m16n8k16.row.col.f32.bf16.bf16.f32 {%0,%1,%2,%3}, {%4,%5,%6,%7}, {%8,%9}, {%0,%1,%2,%3};"
        : "+f"(c[0]), "+f"(c[1]), "+f"(c[2]), "+f"(c[3])
        : "r"(a[0]), "r"(a[1]), "r"(a[2]), "r"(a[3]), "r"(b[0]), "r"(b[1]));
}
__device__ __forceinline__ void ldsm_x4(uint32_t* r, uint32_t addr) {
    asm volatile("ldmatrix.sync.aligned.m8n8.x4.shared.b16 {%0,%1,%2,%3}, [%4];"
        : "=r"(r[0]), "=r"(r[1]), "=r"(r[2]), "=r"(r[3]) : "r"(addr));
}
__device__ __forceinline__ void ldsm_x4_t(uint32_t* r, uint32_t addr) {
    asm volatile("ldmatrix.sync.aligned.m8n8.x4.trans.shared.b16 {%0,%1,%2,%3}, [%4];"
        : "=r"(r[0]), "=r"(r[1]), "=r"(r[2]), "=r"(r[3]) : "r"(addr));
}
__device__ __forceinline__ void ldsm_x2(uint32_t* r, uint32_t addr) {
    asm volatile("ldmatrix.sync.aligned.m8n8.x2.shared.b16 {%0,%1}, [%2];"
        : "=r"(r[0]), "=r"(r[1]) : "r"(addr));
}
__device__ __forceinline__ void cp_async16(uint32_t saddr, const void* g) {
    asm volatile("cp.async.cg.shared.global [%0], [%1], 16;" :: "r"(saddr), "l"(g));
}
__device__ __forceinline__ void cp_async16_zfill(uint32_t saddr, const void* g, bool valid) {
    int sz = valid ? 16 : 0;
    asm volatile("cp.async.cg.shared.global [%0], [%1], 16, %2;" :: "r"(saddr), "l"(g), "r"(sz));
}
__device__ __forceinline__ void cp_async_commit() { asm volatile("cp.async.commit_group;"); }
template <int N> __device__ __forceinline__ void cp_async_wait() { asm volatile("cp.async.wait_group %0;" :: "n"(N)); }

__device__ __forceinline__ float gelu_tanh(float x) {
    const float k0 = 0.7978845608028654f, k1 = 0.044715f;
    float inner = k0 * (x + k1 * x * x * x);
    return 0.5f * x * (1.f + tanhf(inner));
}

__global__ void __launch_bounds__(256) mod_kernel(const bf16* __restrict__ c, const bf16* __restrict__ w_mod) {
    __shared__ float sc[DM];
    __shared__ float part[32][65];
    int tid = threadIdx.x;
    for (int d = tid; d < DM; d += 256) {
        float cv = __bfloat162float(c[d]);
        sc[d] = bfr(cv / (1.f + expf(-cv)));
    }
    __syncthreads();
    int col0 = blockIdx.x * 64;
    int dg = tid >> 3, cg = tid & 7;
    float acc[8];
#pragma unroll
    for (int q = 0; q < 8; ++q) acc[q] = 0.f;
    for (int dd = 0; dd < 16; ++dd) {
        int d = dg * 16 + dd;
        uint4 v = *reinterpret_cast<const uint4*>(w_mod + (size_t)d * (6*DM) + col0 + cg * 8);
        const uint32_t* u = reinterpret_cast<const uint32_t*>(&v);
        float s = sc[d];
#pragma unroll
        for (int q = 0; q < 4; ++q) { float2 f = unpack_bf16(u[q]); acc[2*q] += s * f.x; acc[2*q+1] += s * f.y; }
    }
#pragma unroll
    for (int q = 0; q < 8; ++q) part[dg][cg*8+q] = acc[q];
    __syncthreads();
    if (tid < 64) {
        float s = 0.f;
        for (int g = 0; g < 32; ++g) s += part[g][tid];
        g_mod[col0 + tid] = bfr(s);
    }
    for (int idx = blockIdx.x * 256 + tid; idx < NSEG*MEMN*DM; idx += gridDim.x * 256) g_acc[idx] = 0ull;
}

__device__ __forceinline__ void ln_row16(float* x  ) {
    float s = 0.f;
#pragma unroll
    for (int i = 0; i < 16; ++i) s += x[i];
#pragma unroll
    for (int o = 16; o > 0; o >>= 1) s += __shfl_xor_sync(0xffffffffu, s, o);
    float mean = s * (1.f / DM);
    float q = 0.f;
#pragma unroll
    for (int i = 0; i < 16; ++i) { float d = x[i] - mean; q += d * d; }
#pragma unroll
    for (int o = 16; o > 0; o >>= 1) q += __shfl_xor_sync(0xffffffffu, q, o);
    float m = bfr(mean);
    float v = bfr(q * (1.f / DM));
    float den = bfr(sqrtf(bfr(v + 1e-5f)));
#pragma unroll
    for (int i = 0; i < 16; ++i) x[i] = bfr(bfr(x[i] - m) / den);
}
__device__ __forceinline__ void load_row16(const bf16* p, int lane, float* x) {
#pragma unroll
    for (int h = 0; h < 2; ++h) {
        uint4 v = *reinterpret_cast<const uint4*>(p + h * 256 + lane * 8);
        const uint32_t* u = reinterpret_cast<const uint32_t*>(&v);
#pragma unroll
        for (int q = 0; q < 4; ++q) { float2 f = unpack_bf16(u[q]); x[h*8+2*q] = f.x; x[h*8+2*q+1] = f.y; }
    }
}
__device__ __forceinline__ void store_row16(bf16* p, int lane, const float* x) {
#pragma unroll
    for (int h = 0; h < 2; ++h) {
        uint4 v; uint32_t* u = reinterpret_cast<uint32_t*>(&v);
#pragma unroll
        for (int q = 0; q < 4; ++q) u[q] = pack_bf16(x[h*8+2*q], x[h*8+2*q+1]);
        *reinterpret_cast<uint4*>(p + h * 256 + lane * 8) = v;
    }
}
__device__ __forceinline__ void modulate_row16(float* x, int lane, const float* shift, const float* scale) {
#pragma unroll
    for (int h = 0; h < 2; ++h)
#pragma unroll
        for (int q = 0; q < 8; ++q) {
            int col = h * 256 + lane * 8 + q;
            float t = bfr(x[h*8+q] * bfr(1.f + scale[col]));
            x[h*8+q] = bfr(t + shift[col]);
        }
}

__global__ void __launch_bounds__(256) ln1_kernel(const bf16* __restrict__ x) {
    int warp = (blockIdx.x * 256 + threadIdx.x) >> 5, lane = threadIdx.x & 31;
    if (warp >= S_LEN) return;
    float v[16];
    load_row16(x + (size_t)warp * DM, lane, v);
    ln_row16(v);
    modulate_row16(v, lane, g_mod + 0*DM, g_mod + 1*DM);
    store_row16(g_h1 + (size_t)warp * DM, lane, v);
}
__global__ void __launch_bounds__(256) ln2_kernel() {
    int warp = (blockIdx.x * 256 + threadIdx.x) >> 5, lane = threadIdx.x & 31;
    if (warp >= S_LEN) return;
    float v[16];
    load_row16(g_x2 + (size_t)warp * DM, lane, v);
    ln_row16(v);
    modulate_row16(v, lane, g_mod + 3*DM, g_mod + 4*DM);
    store_row16(g_h2 + (size_t)warp * DM, lane, v);
    ln_row16(v);
    store_row16(g_a1 + (size_t)warp * DM, lane, v);
}
__global__ void __launch_bounds__(256) ln3_kernel() {
    int warp = (blockIdx.x * 256 + threadIdx.x) >> 5, lane = threadIdx.x & 31;
    if (warp >= S_LEN) return;
    float v[16];
    load_row16(g_x1 + (size_t)warp * DM, lane, v);
    ln_row16(v);
    store_row16(g_a3 + (size_t)warp * DM, lane, v);
}

template <int BM, int BN, int WARPS_M, int WARPS_N, int STAGES, class P>
__global__ void __launch_bounds__(WARPS_M*WARPS_N*32) gemm_kernel(P p) {
    constexpr int BK = 32;
    constexpr int NT = WARPS_M * WARPS_N * 32;
    constexpr int LDA = BK + 8, LDB = BN + 8;
    constexpr int WM = BM / WARPS_M, WN = BN / WARPS_N;
    constexpr int MT = WM / 16, NTL = WN / 8;
    extern __shared__ __align__(16) unsigned char smem_raw[];
    bf16* sA = reinterpret_cast<bf16*>(smem_raw);
    bf16* sB = sA + STAGES * BM * LDA;

    const int tid = threadIdx.x, lane = tid & 31, warp = tid >> 5;
    const int wm = warp / WARPS_N, wn = warp % WARPS_N;
    const int m0 = blockIdx.x * BM, n0 = blockIdx.y * BN;
    const int KT = p.K / BK;

    auto load_stage = [&](int st, int kt) {
        for (int c = tid; c < BM * 4; c += NT) {
            int r = c >> 2, ch = c & 3;
            bool valid; const bf16* src = p.a_ptr(m0 + r, kt * BK + ch * 8, valid);
            cp_async16_zfill(smem_u32(sA + (st * BM + r) * LDA + ch * 8), src, valid);
        }
        for (int c = tid; c < BK * (BN / 8); c += NT) {
            int r = c / (BN / 8), ch = c % (BN / 8);
            bool valid = (n0 + ch * 8) < p.N;
            const bf16* src = p.b_ptr(kt * BK + r, valid ? (n0 + ch * 8) : 0);
            cp_async16_zfill(smem_u32(sB + (st * BK + r) * LDB + ch * 8), src, valid);
        }
    };

    float acc[MT][NTL][4];
#pragma unroll
    for (int i = 0; i < MT; ++i)
#pragma unroll
        for (int j = 0; j < NTL; ++j) { acc[i][j][0] = acc[i][j][1] = acc[i][j][2] = acc[i][j][3] = 0.f; }

#pragma unroll
    for (int s = 0; s < STAGES - 1; ++s) { if (s < KT) load_stage(s, s); cp_async_commit(); }

    for (int kt = 0; kt < KT; ++kt) {
        cp_async_wait<STAGES - 2>();
        __syncthreads();
        int nk = kt + STAGES - 1;
        if (nk < KT) load_stage(nk % STAGES, nk);
        cp_async_commit();
        const bf16* a_s = sA + (kt % STAGES) * BM * LDA;
        const bf16* b_s = sB + (kt % STAGES) * BK * LDB;
#pragma unroll
        for (int kk = 0; kk < 2; ++kk) {
            uint32_t af[MT][4], bfr_[NTL][2];
#pragma unroll
            for (int i = 0; i < MT; ++i) {
                int r = wm * WM + i * 16 + (lane & 7) + ((lane >> 3) & 1) * 8;
                int cidx = kk * 16 + (lane >> 4) * 8;
                ldsm_x4(af[i], smem_u32(a_s + r * LDA + cidx));
            }
#pragma unroll
            for (int j = 0; j < NTL; j += 2) {
                int r = kk * 16 + (lane & 7) + ((lane >> 3) & 1) * 8;
                int cidx = wn * WN + j * 8 + (lane >> 4) * 8;
                uint32_t t[4];
                ldsm_x4_t(t, smem_u32(b_s + r * LDB + cidx));
                bfr_[j][0] = t[0]; bfr_[j][1] = t[1]; bfr_[j+1][0] = t[2]; bfr_[j+1][1] = t[3];
            }
#pragma unroll
            for (int i = 0; i < MT; ++i)
#pragma unroll
                for (int j = 0; j < NTL; ++j) mma16816(acc[i][j], af[i], bfr_[j]);
        }
    }
    cp_async_wait<0>();
#pragma unroll
    for (int i = 0; i < MT; ++i)
#pragma unroll
        for (int j = 0; j < NTL; ++j) {
            int r = m0 + wm * WM + i * 16 + (lane >> 2);
            int c = n0 + wn * WN + j * 8 + (lane & 3) * 2;
            if (c < p.N) {
                p.epi(r, c, acc[i][j][0], acc[i][j][1]);
                p.epi(r + 8, c, acc[i][j][2], acc[i][j][3]);
            }
        }
}

struct PQKV {
    const bf16 *wq, *wk, *wv; int N, K;
    __device__ const bf16* a_ptr(int r, int k, bool& valid) const { valid = true; return g_h1 + (size_t)r * DM + k; }
    __device__ const bf16* b_ptr(int k, int n) const {
        int sel = n / HD; const bf16* w = sel == 0 ? wq : (sel == 1 ? wk : wv);
        return w + (size_t)k * HD + (n - sel * HD);
    }
    __device__ void epi(int r, int c, float v0, float v1) const {
        *reinterpret_cast<uint32_t*>(g_qkv + (size_t)r * (3*HD) + c) = pack_bf16(v0, v1);
    }
};
struct POut {
    const bf16 *wo, *x; int N, K;
    __device__ const bf16* a_ptr(int r, int k, bool& valid) const { valid = true; return g_o + (size_t)r * HD + k; }
    __device__ const bf16* b_ptr(int k, int n) const { return wo + (size_t)k * DM + n; }
    __device__ void epi(int r, int c, float v0, float v1) const {
        float2 xv = unpack_bf16(*reinterpret_cast<const uint32_t*>(x + (size_t)r * DM + c));
        float ga0 = g_mod[2*DM + c], ga1 = g_mod[2*DM + c + 1];
        float o0 = bfr(xv.x + bfr(ga0 * bfr(v0)));
        float o1 = bfr(xv.y + bfr(ga1 * bfr(v1)));
        *reinterpret_cast<uint32_t*>(g_x2 + (size_t)r * DM + c) = pack_bf16(o0, o1);
    }
};
struct PW1 {
    const bf16 *w; int N, K;
    __device__ const bf16* a_ptr(int r, int k, bool& valid) const { valid = true; return g_a1 + (size_t)r * DM + k; }
    __device__ const bf16* b_ptr(int k, int n) const { return w + (size_t)k * DM + n; }
    __device__ void epi(int r, int c, float v0, float v1) const {
        *reinterpret_cast<uint32_t*>(g_g + (size_t)r * DM + c) = pack_bf16(gelu_tanh(bfr(v0)), gelu_tanh(bfr(v1)));
    }
};
struct PW2 {
    const bf16 *w; int N, K;
    __device__ const bf16* a_ptr(int r, int k, bool& valid) const {
        int q = k >> 7;
        int src = r + (q == 0 ? -1 : (q == 1 ? 1 : (q == 2 ? -2 : 2)));
        valid = (src >= 0) && (src < S_LEN);
        return g_g + (size_t)(valid ? src : 0) * DM + k;
    }
    __device__ const bf16* b_ptr(int k, int n) const { return w + (size_t)k * DM + n; }
    __device__ void epi(int r, int c, float v0, float v1) const {
        float2 hv = unpack_bf16(*reinterpret_cast<const uint32_t*>(g_h2 + (size_t)r * DM + c));
        *reinterpret_cast<uint32_t*>(g_x1 + (size_t)r * DM + c) = pack_bf16(hv.x + bfr(v0), hv.y + bfr(v1));
    }
};
struct PW3 {
    const bf16 *w; int N, K;
    __device__ const bf16* a_ptr(int r, int k, bool& valid) const { valid = true; return g_a3 + (size_t)r * DM + k; }
    __device__ const bf16* b_ptr(int k, int n) const { return w + (size_t)k * FF + n; }
    __device__ void epi(int r, int c, float v0, float v1) const {
        *reinterpret_cast<uint32_t*>(g_u + (size_t)r * FF + c) = pack_bf16(gelu_tanh(bfr(v0)), gelu_tanh(bfr(v1)));
    }
};
struct PW4 {
    const bf16 *w; bf16* out; int N, K;
    __device__ const bf16* a_ptr(int r, int k, bool& valid) const { valid = true; return g_u + (size_t)r * FF + k; }
    __device__ const bf16* b_ptr(int k, int n) const { return w + (size_t)k * DM + n; }
    __device__ void epi(int r, int c, float v0, float v1) const {
        float2 x1 = unpack_bf16(*reinterpret_cast<const uint32_t*>(g_x1 + (size_t)r * DM + c));
        float2 x2 = unpack_bf16(*reinterpret_cast<const uint32_t*>(g_x2 + (size_t)r * DM + c));
        float gb0 = g_mod[5*DM + c], gb1 = g_mod[5*DM + c + 1];
        float b0 = bfr(x1.x + bfr(v0)), b1 = bfr(x1.y + bfr(v1));
        float o0 = bfr(x2.x + bfr(gb0 * b0)), o1 = bfr(x2.y + bfr(gb1 * b1));
        *reinterpret_cast<uint32_t*>(out + (size_t)r * DM + c) = pack_bf16(o0, o1);
    }
};

#define CH_LDM   (DM + 8)
#define CH_LDW   (64 + 8)
#define CH_LDO   (256 + 8)
#define CH_LDP   (48 + 8)
#define CH_LDOS  (DH + 8)
struct ChainSmem {
    bf16  mem_s[MEMN * CH_LDM];
    bf16  wv_s[DM * CH_LDW];
    bf16  wo_s[DH * CH_LDO];
    bf16  q_s[MEMN * CH_LDW];
    bf16  k_s[2][48 * CH_LDW];
    bf16  v_s[2][48 * CH_LDW];
    float xs[2][40 * 8];
    bf16  p_s[MEMN * CH_LDP];
    bf16  o_s[MEMN * CH_LDOS];
    unsigned long long mbar[2];
};
#define FIX_SCALE 1073741824.0f

__device__ __forceinline__ void mbar_wait(uint32_t mb, uint32_t parity) {
    uint32_t ok; int it = 0;
    do {
        asm volatile("{\n.reg .pred p;\nmbarrier.try_wait.parity.shared::cta.b64 p, [%1], %2;\nselp.u32 %0,1,0,p;\n}"
            : "=r"(ok) : "r"(mb), "r"(parity) : "memory");
        if (++it > (1 << 24)) asm volatile("trap;");
    } while (!ok);
}

__global__ void __cluster_dims__(2,1,1) __launch_bounds__(256, 1)
chain_kernel(const bf16* __restrict__ mem0, const bf16* __restrict__ Wq, const bf16* __restrict__ Wk,
             const bf16* __restrict__ Wv, const bf16* __restrict__ Wo) {
    extern __shared__ __align__(16) unsigned char smem_raw[];
    ChainSmem& sm = *reinterpret_cast<ChainSmem*>(smem_raw);
    const int tid = threadIdx.x, lane = tid & 31, warp = tid >> 5;
    const int h = blockIdx.x >> 1, ih = blockIdx.x & 1;
    const int g = lane >> 2, t4 = lane & 3;
    const int ecol0 = h * DH + ih * 64;

    uint32_t wqk[32][4];
    {
        for (int sel = 0; sel < 2; ++sel) {
            const bf16* W = sel == 0 ? Wq : Wk;
            __syncthreads();
            for (int c = tid; c < DM * 8; c += 256) {
                int r = c >> 3, ch = c & 7;
                cp_async16(smem_u32(sm.wv_s + r * CH_LDW + ch * 8), W + (size_t)r * HD + ecol0 + ch * 8);
            }
            cp_async_commit(); cp_async_wait<0>();
            __syncthreads();
            if ((warp >> 2) == sel) {
                int et = warp & 3;
#pragma unroll
                for (int kk = 0; kk < 32; ++kk) {
                    int r = kk * 16 + (lane & 7) + (lane >> 4) * 8;
                    int cidx = et * 16 + ((lane >> 3) & 1) * 8;
                    ldsm_x4_t(wqk[kk], smem_u32(sm.wv_s + r * CH_LDW + cidx));
                }
            }
        }
        __syncthreads();
    }
    for (int c = tid; c < DM * 8; c += 256) {
        int r = c >> 3, ch = c & 7;
        cp_async16(smem_u32(sm.wv_s + r * CH_LDW + ch * 8), Wv + (size_t)r * HD + ecol0 + ch * 8);
    }
    for (int c = tid; c < DH * 32; c += 256) {
        int r = c >> 5, ch = c & 31;
        cp_async16(smem_u32(sm.wo_s + r * CH_LDO + ch * 8), Wo + (size_t)(h * DH + r) * DM + ih * 256 + ch * 8);
    }
    for (int c = tid; c < MEMN * 64; c += 256) {
        int r = c >> 6, ch = c & 63;
        cp_async16(smem_u32(sm.mem_s + r * CH_LDM + ch * 8), mem0 + r * DM + ch * 8);
    }
    auto prefetch_kv = [&](int seg, int buf) {
        for (int c = tid; c < 2 * SEG * 8; c += 256) {
            int which = c >> 8, r = (c >> 3) & 31, ch = c & 7;
            const bf16* src = g_qkv + (size_t)(seg * SEG + r) * (3*HD) + (1 + which) * HD + ecol0 + ch * 8;
            bf16* dst = (which == 0 ? sm.k_s[buf] : sm.v_s[buf]) + (8 + r) * CH_LDW + ch * 8;
            cp_async16(smem_u32(dst), src);
        }
    };
    prefetch_kv(0, 0);
    cp_async_commit();
    for (int c = tid; c < 2 * 2 * 8 * CH_LDW; c += 256) {
        int b = c / (2 * 8 * CH_LDW), rem = c % (2 * 8 * CH_LDW), which = rem / (8 * CH_LDW), off = rem % (8 * CH_LDW);
        (which == 0 ? sm.k_s[b] : sm.v_s[b])[40 * CH_LDW + off] = __float2bfloat16(0.f);
    }
    for (int c = tid; c < MEMN * CH_LDP; c += 256) sm.p_s[c] = __float2bfloat16(0.f);
    const uint32_t mb1 = smem_u32(&sm.mbar[0]), mb2 = smem_u32(&sm.mbar[1]);
    if (tid == 0) {
        asm volatile("mbarrier.init.shared::cta.b64 [%0], 1;" :: "r"(mb1));
        asm volatile("mbarrier.init.shared::cta.b64 [%0], 1;" :: "r"(mb2));
        asm volatile("fence.mbarrier_init.release.cluster;" ::: "memory");
    }
    cp_async_wait<0>();
    asm volatile("barrier.cluster.arrive.release.aligned;\nbarrier.cluster.wait.acquire.aligned;" ::: "memory");
    uint32_t peer_xs, peer_os, peer_mb1, peer_mb2;
    asm volatile("mapa.shared::cluster.u32 %0, %1, %2;" : "=r"(peer_xs)  : "r"(smem_u32(sm.xs[ih])), "r"(ih ^ 1));
    asm volatile("mapa.shared::cluster.u32 %0, %1, %2;" : "=r"(peer_os)  : "r"(smem_u32(sm.o_s)), "r"(ih ^ 1));
    asm volatile("mapa.shared::cluster.u32 %0, %1, %2;" : "=r"(peer_mb1) : "r"(mb1), "r"(ih ^ 1));
    asm volatile("mapa.shared::cluster.u32 %0, %1, %2;" : "=r"(peer_mb2) : "r"(mb2), "r"(ih ^ 1));
    const uint32_t own_xs = smem_u32(sm.xs[ih]), own_os = smem_u32(sm.o_s);

    const float scale = 0.08838834764831845f;

    for (int s = 0; s < NSEG; ++s) {
        const int buf = s & 1;
        const bool last = (s == NSEG - 1);
        if (tid == 0 && !last) {
            asm volatile("mbarrier.arrive.expect_tx.shared::cta.b64 _, [%0], %1;" :: "r"(mb1), "r"(2 * 40 * 8 * 4) : "memory");
            asm volatile("mbarrier.arrive.expect_tx.shared::cta.b64 _, [%0], %1;" :: "r"(mb2), "r"(MEMN * DH * 2) : "memory");
        }
        if (!last) prefetch_kv(s + 1, buf ^ 1);
        cp_async_commit();

        {
            float c4[4][4];
#pragma unroll
            for (int i = 0; i < 4; ++i) { c4[i][0] = c4[i][1] = c4[i][2] = c4[i][3] = 0.f; }
#pragma unroll
            for (int kk = 0; kk < 32; kk += 2) {
                uint32_t b4[4];
                ldsm_x4(b4, smem_u32(sm.mem_s + (lane & 7) * CH_LDM + kk * 16 + (lane >> 3) * 8));
                mma16816(c4[kk & 3], wqk[kk], b4);
                mma16816(c4[(kk + 1) & 3], wqk[kk + 1], b4 + 2);
            }
            float r0 = c4[0][0] + c4[1][0] + c4[2][0] + c4[3][0];
            float r1 = c4[0][1] + c4[1][1] + c4[2][1] + c4[3][1];
            float r2 = c4[0][2] + c4[1][2] + c4[2][2] + c4[3][2];
            float r3 = c4[0][3] + c4[1][3] + c4[2][3] + c4[3][3];
            int e0 = (warp & 3) * 16 + g;
            bf16* dst = (warp < 4) ? sm.q_s : sm.k_s[buf];
            dst[(2*t4)   * CH_LDW + e0]     = __float2bfloat16_rn(r0);
            dst[(2*t4+1) * CH_LDW + e0]     = __float2bfloat16_rn(r1);
            dst[(2*t4)   * CH_LDW + e0 + 8] = __float2bfloat16_rn(r2);
            dst[(2*t4+1) * CH_LDW + e0 + 8] = __float2bfloat16_rn(r3);
        }
        cp_async_wait<1>();
        __syncthreads();

        if (warp >= 4) {
            int et = warp - 4;
            float c2[2][4];
#pragma unroll
            for (int i = 0; i < 2; ++i) { c2[i][0] = c2[i][1] = c2[i][2] = c2[i][3] = 0.f; }
#pragma unroll 4
            for (int kk = 0; kk < 32; kk += 2) {
                uint32_t b4[4], a0[4], a1[4];
                ldsm_x4(b4, smem_u32(sm.mem_s + (lane & 7) * CH_LDM + kk * 16 + (lane >> 3) * 8));
                int r = kk * 16 + (lane & 7) + (lane >> 4) * 8;
                int cidx = et * 16 + ((lane >> 3) & 1) * 8;
                ldsm_x4_t(a0, smem_u32(sm.wv_s + r * CH_LDW + cidx));
                ldsm_x4_t(a1, smem_u32(sm.wv_s + (r + 16) * CH_LDW + cidx));
                mma16816(c2[0], a0, b4);
                mma16816(c2[1], a1, b4 + 2);
            }
            int e0 = et * 16 + g;
            bf16* dst = sm.v_s[buf];
            dst[(2*t4)   * CH_LDW + e0]     = __float2bfloat16_rn(c2[0][0] + c2[1][0]);
            dst[(2*t4+1) * CH_LDW + e0]     = __float2bfloat16_rn(c2[0][1] + c2[1][1]);
            dst[(2*t4)   * CH_LDW + e0 + 8] = __float2bfloat16_rn(c2[0][2] + c2[1][2]);
            dst[(2*t4+1) * CH_LDW + e0 + 8] = __float2bfloat16_rn(c2[0][3] + c2[1][3]);
        } else if (!last) {
            if (warp < 3) {
                float c[4] = {0.f, 0.f, 0.f, 0.f};
#pragma unroll
                for (int kk = 0; kk < 4; kk += 2) {
                    uint32_t b4[4], a0[4], a1[4];
                    ldsm_x4(b4, smem_u32(sm.q_s + (lane & 7) * CH_LDW + kk * 16 + (lane >> 3) * 8));
                    int r = warp * 16 + (lane & 7) + ((lane >> 3) & 1) * 8;
                    ldsm_x4(a0, smem_u32(sm.k_s[buf] + r * CH_LDW + kk * 16 + (lane >> 4) * 8));
                    ldsm_x4(a1, smem_u32(sm.k_s[buf] + r * CH_LDW + (kk + 1) * 16 + (lane >> 4) * 8));
                    mma16816(c, a0, b4);
                    mma16816(c, a1, b4 + 2);
                }
                int key = warp * 16 + g;
                uint32_t off = (key * 8 + 2 * t4) * 4;
                asm volatile("st.async.shared::cluster.mbarrier::complete_tx::bytes.v2.f32 [%0], {%1,%2}, [%3];"
                    :: "r"(own_xs + off), "f"(c[0]), "f"(c[1]), "r"(mb1) : "memory");
                asm volatile("st.async.shared::cluster.mbarrier::complete_tx::bytes.v2.f32 [%0], {%1,%2}, [%3];"
                    :: "r"(peer_xs + off), "f"(c[0]), "f"(c[1]), "r"(peer_mb1) : "memory");
                if (warp < 2) {
                    off += 8 * 8 * 4;
                    asm volatile("st.async.shared::cluster.mbarrier::complete_tx::bytes.v2.f32 [%0], {%1,%2}, [%3];"
                        :: "r"(own_xs + off), "f"(c[2]), "f"(c[3]), "r"(mb1) : "memory");
                    asm volatile("st.async.shared::cluster.mbarrier::complete_tx::bytes.v2.f32 [%0], {%1,%2}, [%3];"
                        :: "r"(peer_xs + off), "f"(c[2]), "f"(c[3]), "r"(peer_mb1) : "memory");
                }
            }
            mbar_wait(mb1, s & 1);
            {
                int row = warp * 2 + (lane >> 4), l = lane & 15;
                float sc[3]; float mx = -3.0e38f;
#pragma unroll
                for (int q = 0; q < 3; ++q) {
                    int key = l + q * 16;
                    if (key < 40) {
                        float v = sm.xs[0][key * 8 + row] + sm.xs[1][key * 8 + row];
                        v = bfr(bfr(v) * scale);
                        sc[q] = v; mx = fmaxf(mx, v);
                    } else sc[q] = 0.f;
                }
#pragma unroll
                for (int o = 8; o > 0; o >>= 1) mx = fmaxf(mx, __shfl_xor_sync(0xffffffffu, mx, o));
                float sum = 0.f;
#pragma unroll
                for (int q = 0; q < 3; ++q) { int key = l + q * 16; if (key < 40) { sc[q] = expf(sc[q] - mx); sum += sc[q]; } }
#pragma unroll
                for (int o = 8; o > 0; o >>= 1) sum += __shfl_xor_sync(0xffffffffu, sum, o);
                float inv = 1.f / sum;
#pragma unroll
                for (int q = 0; q < 3; ++q) { int key = l + q * 16; if (key < 40) sm.p_s[row * CH_LDP + key] = __float2bfloat16_rn(sc[q] * inv); }
            }
        }
        __syncthreads();
        if (warp >= 4) {
            int c = tid - 128;
            int which = c >> 6, r = (c >> 3) & 7, ch = c & 7;
            const bf16* src = (which == 0 ? sm.k_s[buf] : sm.v_s[buf]) + r * CH_LDW + ch * 8;
            bf16* dst = (which == 0 ? g_km : g_vm) + (size_t)(s * MEMN + r) * HD + ecol0 + ch * 8;
            *reinterpret_cast<uint4*>(dst) = *reinterpret_cast<const uint4*>(src);
        }
        if (last) break;

        if (warp < 4) {
            float c[4] = {0.f, 0.f, 0.f, 0.f};
#pragma unroll
            for (int kk = 0; kk < 3; ++kk) {
                uint32_t a[4], b2[2];
                int r = kk * 16 + (lane & 7) + (lane >> 4) * 8;
                int cidx = warp * 16 + ((lane >> 3) & 1) * 8;
                ldsm_x4_t(a, smem_u32(sm.v_s[buf] + r * CH_LDW + cidx));
                ldsm_x2(b2, smem_u32(sm.p_s + (lane & 7) * CH_LDP + kk * 16 + ((lane >> 3) & 1) * 8));
                mma16816(c, a, b2);
            }
            uint32_t lo = pack_bf16(c[0], c[1]), hi = pack_bf16(c[2], c[3]);
            uint32_t tlo, thi;
            asm volatile("movmatrix.sync.aligned.m8n8.trans.b16 %0, %1;" : "=r"(tlo) : "r"(lo));
            asm volatile("movmatrix.sync.aligned.m8n8.trans.b16 %0, %1;" : "=r"(thi) : "r"(hi));
            uint32_t off = (g * CH_LDOS + ih * 64 + warp * 16 + 2 * t4) * 2;
            asm volatile("st.async.shared::cluster.mbarrier::complete_tx::bytes.b32 [%0], %1, [%2];" :: "r"(own_os + off), "r"(tlo), "r"(mb2) : "memory");
            asm volatile("st.async.shared::cluster.mbarrier::complete_tx::bytes.b32 [%0], %1, [%2];" :: "r"(own_os + off + 16), "r"(thi), "r"(mb2) : "memory");
            asm volatile("st.async.shared::cluster.mbarrier::complete_tx::bytes.b32 [%0], %1, [%2];" :: "r"(peer_os + off), "r"(tlo), "r"(peer_mb2) : "memory");
            asm volatile("st.async.shared::cluster.mbarrier::complete_tx::bytes.b32 [%0], %1, [%2];" :: "r"(peer_os + off + 16), "r"(thi), "r"(peer_mb2) : "memory");
        }
        mbar_wait(mb2, s & 1);

        unsigned long long* acc = g_acc + (size_t)s * (MEMN * DM);
        {
#pragma unroll
            for (int mt = 0; mt < 2; ++mt) {
                float c[4] = {0.f, 0.f, 0.f, 0.f};
                int mtile = warp * 2 + mt;
#pragma unroll
                for (int kk = 0; kk < 8; kk += 2) {
                    uint32_t b4[4], a0[4], a1[4];
                    ldsm_x4(b4, smem_u32(sm.o_s + (lane & 7) * CH_LDOS + kk * 16 + (lane >> 3) * 8));
                    int r = kk * 16 + (lane & 7) + (lane >> 4) * 8;
                    int cidx = mtile * 16 + ((lane >> 3) & 1) * 8;
                    ldsm_x4_t(a0, smem_u32(sm.wo_s + r * CH_LDO + cidx));
                    ldsm_x4_t(a1, smem_u32(sm.wo_s + (r + 16) * CH_LDO + cidx));
                    mma16816(c, a0, b4);
                    mma16816(c, a1, b4 + 2);
                }
                int dcol = ih * 256 + mtile * 16 + g;
#pragma unroll
                for (int q = 0; q < 4; ++q) {
                    int d = dcol + (q >> 1) * 8, par = q & 1;
                    long long fx = __float2ll_rn(c[q] * FIX_SCALE);
                    unsigned long long w = (1ull << 56) + (unsigned long long)fx;
                    asm volatile("red.relaxed.gpu.global.add.u64 [%0], %1;" :: "l"(acc + par * 2048 + d * 4 + t4), "l"(w) : "memory");
                }
            }
        }
        {
#pragma unroll
            for (int u = 0; u < 2; ++u) {
                int unit = tid + u * 256;
                int par = unit >> 8, dp = unit & 255;
                const unsigned long long* p0 = acc + par * 2048 + (2 * dp) * 4;
                unsigned long long w[8];
                int it = 0;
                for (;;) {
#pragma unroll
                    for (int q = 0; q < 4; ++q)
                        asm volatile("ld.relaxed.gpu.global.v2.u64 {%0,%1}, [%2];" : "=l"(w[2*q]), "=l"(w[2*q+1]) : "l"(p0 + 2*q) : "memory");
                    bool ok = true;
#pragma unroll
                    for (int q = 0; q < 8; ++q) {
                        long long sv = (long long)(w[q] << 8) >> 8;
                        ok = ok && (((w[q] - (unsigned long long)sv) >> 56) == (unsigned long long)NH);
                    }
                    if (ok) break;
                    if (++it > (1 << 22)) asm volatile("trap;");
                }
#pragma unroll
                for (int q = 0; q < 4; ++q) {
                    float v0 = (float)((long long)(w[q] << 8) >> 8) * (1.f / FIX_SCALE);
                    float v1 = (float)((long long)(w[4+q] << 8) >> 8) * (1.f / FIX_SCALE);
                    int n = 2 * q + par;
                    *reinterpret_cast<uint32_t*>(sm.mem_s + n * CH_LDM + 2 * dp) = pack_bf16(v0, v1);
                }
            }
        }
        __syncthreads();
    }
    asm volatile("barrier.cluster.arrive.release.aligned;\nbarrier.cluster.wait.acquire.aligned;" ::: "memory");
}

#define TA_LD (DH + 8)
__global__ void __launch_bounds__(128) tok_attn_kernel() {
    __shared__ __align__(16) bf16 q_s[SEG * TA_LD];
    __shared__ __align__(16) bf16 k_s[48 * TA_LD];
    __shared__ __align__(16) bf16 v_s[48 * TA_LD];
    __shared__ __align__(16) bf16 p_s[SEG * CH_LDP];
    const int seg = blockIdx.x / NH, h = blockIdx.x % NH;
    const int tid = threadIdx.x, lane = tid & 31, warp = tid >> 5;
    const int g = lane >> 2, t4 = lane & 3;
    for (int c = tid; c < SEG * 16; c += 128) {
        int r = c >> 4, ch = c & 15;
        const bf16* base = g_qkv + (size_t)(seg * SEG + r) * (3*HD) + h * DH + ch * 8;
        cp_async16(smem_u32(q_s + r * TA_LD + ch * 8), base);
        cp_async16(smem_u32(k_s + (8 + r) * TA_LD + ch * 8), base + HD);
        cp_async16(smem_u32(v_s + (8 + r) * TA_LD + ch * 8), base + 2*HD);
    }
    for (int c = tid; c < MEMN * 16; c += 128) {
        int r = c >> 4, ch = c & 15;
        size_t off = (size_t)(seg * MEMN + r) * HD + h * DH + ch * 8;
        cp_async16(smem_u32(k_s + r * TA_LD + ch * 8), g_km + off);
        cp_async16(smem_u32(v_s + r * TA_LD + ch * 8), g_vm + off);
    }
    cp_async_commit();
    for (int c = tid; c < 8 * TA_LD; c += 128) { k_s[40 * TA_LD + c] = __float2bfloat16(0.f); v_s[40 * TA_LD + c] = __float2bfloat16(0.f); }
    cp_async_wait<0>();
    __syncthreads();
    const float scale = 0.08838834764831845f;
    {
        int mt = warp & 1, half = warp >> 1;
#pragma unroll
        for (int nt = 0; nt < 3; ++nt) {
            int ntile = half * 3 + nt;
            if (ntile >= 5) break;
            float c[4] = {0.f, 0.f, 0.f, 0.f};
#pragma unroll
            for (int kk = 0; kk < 8; ++kk) {
                uint32_t a[4], b2[2];
                int r = mt * 16 + (lane & 7) + ((lane >> 3) & 1) * 8;
                ldsm_x4(a, smem_u32(q_s + r * TA_LD + kk * 16 + (lane >> 4) * 8));
                ldsm_x2(b2, smem_u32(k_s + (ntile * 8 + (lane & 7)) * TA_LD + kk * 16 + ((lane >> 3) & 1) * 8));
                mma16816(c, a, b2);
            }
#pragma unroll
            for (int q = 0; q < 4; ++q) {
                int row = mt * 16 + g + (q >> 1) * 8, key = ntile * 8 + 2 * t4 + (q & 1);
                float v = bfr(bfr(c[q]) * scale);
                p_s[row * CH_LDP + key] = __float2bfloat16_rn(v);
            }
        }
    }
    __syncthreads();
    {
        int row = warp * 8 + (lane >> 2), l = lane & 3;
        float sc[10]; float mx = -3.0e38f;
#pragma unroll
        for (int q = 0; q < 10; ++q) {
            int key = l * 10 + q;
            float v = __bfloat162float(p_s[row * CH_LDP + key]);
            if (key > row + 8) v = -1.0e9f;
            sc[q] = v; mx = fmaxf(mx, v);
        }
        mx = fmaxf(mx, __shfl_xor_sync(0xffffffffu, mx, 1));
        mx = fmaxf(mx, __shfl_xor_sync(0xffffffffu, mx, 2));
        float sum = 0.f;
#pragma unroll
        for (int q = 0; q < 10; ++q) { sc[q] = expf(sc[q] - mx); sum += sc[q]; }
        sum += __shfl_xor_sync(0xffffffffu, sum, 1);
        sum += __shfl_xor_sync(0xffffffffu, sum, 2);
        float inv = 1.f / sum;
#pragma unroll
        for (int q = 0; q < 10; ++q) p_s[row * CH_LDP + l * 10 + q] = __float2bfloat16_rn(sc[q] * inv);
        if (l == 0) {
#pragma unroll
            for (int q = 40; q < 48; ++q) p_s[row * CH_LDP + q] = __float2bfloat16(0.f);
        }
    }
    __syncthreads();
    {
        int mt = warp & 1, eh = warp >> 1;
        uint32_t a[3][4];
#pragma unroll
        for (int kk = 0; kk < 3; ++kk) {
            int r = mt * 16 + (lane & 7) + ((lane >> 3) & 1) * 8;
            ldsm_x4(a[kk], smem_u32(p_s + r * CH_LDP + kk * 16 + (lane >> 4) * 8));
        }
#pragma unroll
        for (int nt = 0; nt < 8; nt += 2) {
            float c0[4] = {0.f,0.f,0.f,0.f}, c1[4] = {0.f,0.f,0.f,0.f};
#pragma unroll
            for (int kk = 0; kk < 3; ++kk) {
                uint32_t t[4];
                int r = kk * 16 + (lane & 7) + ((lane >> 3) & 1) * 8;
                ldsm_x4_t(t, smem_u32(v_s + r * TA_LD + eh * 64 + nt * 8 + (lane >> 4) * 8));
                mma16816(c0, a[kk], t);
                mma16816(c1, a[kk], t + 2);
            }
            int row = seg * SEG + mt * 16 + g;
            int col = h * DH + eh * 64 + nt * 8 + 2 * t4;
            *reinterpret_cast<uint32_t*>(g_o + (size_t)row * HD + col) = pack_bf16(c0[0], c0[1]);
            *reinterpret_cast<uint32_t*>(g_o + (size_t)(row + 8) * HD + col) = pack_bf16(c0[2], c0[3]);
            *reinterpret_cast<uint32_t*>(g_o + (size_t)row * HD + col + 8) = pack_bf16(c1[0], c1[1]);
            *reinterpret_cast<uint32_t*>(g_o + (size_t)(row + 8) * HD + col + 8) = pack_bf16(c1[2], c1[3]);
        }
    }
}

template <int BM, int BN, int WARPS_M, int WARPS_N, int STAGES, class P>
static void launch_gemm(const P& p, int M, cudaStream_t st) {
    constexpr int smem = STAGES * (BM * (32 + 8) + 32 * (BN + 8)) * 2;
    auto kern = gemm_kernel<BM, BN, WARPS_M, WARPS_N, STAGES, P>;
    cudaFuncSetAttribute(kern, cudaFuncAttributeMaxDynamicSharedMemorySize, smem);
    dim3 grid(M / BM, (p.N + BN - 1) / BN);
    kern<<<grid, WARPS_M * WARPS_N * 32, smem, st>>>(p);
}

extern "C" void kernel_launch(void* const* d_in, const int* in_sizes, int n_in, void* d_out, int out_size) {
    const bf16* x     = (const bf16*)d_in[0];
    const bf16* mem0  = (const bf16*)d_in[1];
    const bf16* Wq    = (const bf16*)d_in[2];
    const bf16* Wk    = (const bf16*)d_in[3];
    const bf16* Wv    = (const bf16*)d_in[4];
    const bf16* Wo    = (const bf16*)d_in[5];
    const bf16* w1    = (const bf16*)d_in[8];
    const bf16* w2    = (const bf16*)d_in[9];
    const bf16* w3    = (const bf16*)d_in[10];
    const bf16* w4    = (const bf16*)d_in[11];
    const bf16* cvec  = (const bf16*)d_in[12];
    const bf16* w_mod = (const bf16*)d_in[13];
    bf16* out = (bf16*)d_out;
    cudaStream_t st = cudaStreamPerThread;

    mod_kernel<<<(6*DM)/64, 256, 0, st>>>(cvec, w_mod);
    ln1_kernel<<<S_LEN / 8, 256, 0, st>>>(x);
    { PQKV p{Wq, Wk, Wv, 3*HD, DM}; launch_gemm<128,128,2,4,4>(p, S_LEN, st); }
    cudaFuncSetAttribute(chain_kernel, cudaFuncAttributeMaxDynamicSharedMemorySize, (int)sizeof(ChainSmem));
    chain_kernel<<<2*NH, 256, sizeof(ChainSmem), st>>>(mem0, Wq, Wk, Wv, Wo);
    tok_attn_kernel<<<NSEG * NH, 128, 0, st>>>();
    { POut p{Wo, x, DM, HD}; launch_gemm<64,128,2,4,4>(p, S_LEN, st); }
    ln2_kernel<<<S_LEN / 8, 256, 0, st>>>();
    { PW1 p{w1, DM, DM}; launch_gemm<64,128,2,4,4>(p, S_LEN, st); }
    { PW2 p{w2, DM, DM}; launch_gemm<64,128,2,4,4>(p, S_LEN, st); }
    ln3_kernel<<<S_LEN / 8, 256, 0, st>>>();
    { PW3 p{w3, FF, DM}; launch_gemm<128,128,2,4,4>(p, S_LEN, st); }
    { PW4 p{w4, out, DM, FF}; launch_gemm<64,128,2,4,4>(p, S_LEN, st); }
}
```

```cpp
#include <cuda_runtime.h>
#include <cuda_bf16.h>
#include <stdint.h>
#include <cuda.h>

typedef __nv_bfloat16 bf16;

#define S_LEN 2048
#define DM    512
#define NH    32
#define DH    128
#define HD    (NH*DH)
#define MEMN  8
#define SEG   32
#define NSEG  (S_LEN/SEG)
#define FF    1376

__device__ float              g_mod[6*DM];
__device__ bf16               g_h1[S_LEN*DM];
__device__ bf16               g_qkv[(size_t)S_LEN*3*HD];
__device__ bf16               g_km[NSEG*MEMN*HD];
__device__ bf16               g_vm[NSEG*MEMN*HD];
__device__ unsigned long long g_acc[NSEG*MEMN*DM];
__device__ bf16               g_o[(size_t)S_LEN*HD];
__device__ bf16               g_x2[S_LEN*DM];
__device__ bf16               g_h2[S_LEN*DM];
__device__ bf16               g_a1[S_LEN*DM];
__device__ bf16               g_g[S_LEN*DM];
__device__ bf16               g_x1[S_LEN*DM];
__device__ bf16               g_a3[S_LEN*DM];
__device__ bf16               g_u[S_LEN*FF];

__device__ __forceinline__ float bfr(float x) { return __bfloat162float(__float2bfloat16_rn(x)); }
__device__ __forceinline__ uint32_t pack_bf16(float lo, float hi) {
    __nv_bfloat162 v = __floats2bfloat162_rn(lo, hi);
    return *reinterpret_cast<uint32_t*>(&v);
}
__device__ __forceinline__ float2 unpack_bf16(uint32_t u) {
    __nv_bfloat162 v = *reinterpret_cast<__nv_bfloat162*>(&u);
    return make_float2(__bfloat162float(v.x), __bfloat162float(v.y));
}
__device__ __forceinline__ uint32_t smem_u32(const void* p) { return (uint32_t)__cvta_generic_to_shared(p); }

__device__ __forceinline__ void mma16816(float* c, const uint32_t* a, const uint32_t* b) {
    asm volatile("mma.sync.aligned.m16n8k16.row.col.f32.bf16.bf16.f32 {%0,%1,%2,%3}, {%4,%5,%6,%7}, {%8,%9}, {%0,%1,%2,%3};"
        : "+f"(c[0]), "+f"(c[1]), "+f"(c[2]), "+f"(c[3])
        : "r"(a[0]), "r"(a[1]), "r"(a[2]), "r"(a[3]), "r"(b[0]), "r"(b[1]));
}
__device__ __forceinline__ void ldsm_x4(uint32_t* r, uint32_t addr) {
    asm volatile("ldmatrix.sync.aligned.m8n8.x4.shared.b16 {%0,%1,%2,%3}, [%4];"
        : "=r"(r[0]), "=r"(r[1]), "=r"(r[2]), "=r"(r[3]) : "r"(addr));
}
__device__ __forceinline__ void ldsm_x4_t(uint32_t* r, uint32_t addr) {
    asm volatile("ldmatrix.sync.aligned.m8n8.x4.trans.shared.b16 {%0,%1,%2,%3}, [%4];"
        : "=r"(r[0]), "=r"(r[1]), "=r"(r[2]), "=r"(r[3]) : "r"(addr));
}
__device__ __forceinline__ void ldsm_x2(uint32_t* r, uint32_t addr) {
    asm volatile("ldmatrix.sync.aligned.m8n8.x2.shared.b16 {%0,%1}, [%2];"
        : "=r"(r[0]), "=r"(r[1]) : "r"(addr));
}
__device__ __forceinline__ void cp_async16(uint32_t saddr, const void* g) {
    asm volatile("cp.async.cg.shared.global [%0], [%1], 16;" :: "r"(saddr), "l"(g));
}
__device__ __forceinline__ void cp_async16_zfill(uint32_t saddr, const void* g, bool valid) {
    int sz = valid ? 16 : 0;
    asm volatile("cp.async.cg.shared.global [%0], [%1], 16, %2;" :: "r"(saddr), "l"(g), "r"(sz));
}
__device__ __forceinline__ void cp_async_commit() { asm volatile("cp.async.commit_group;"); }
template <int N> __device__ __forceinline__ void cp_async_wait() { asm volatile("cp.async.wait_group %0;" :: "n"(N)); }

__device__ __forceinline__ float gelu_tanh(float x) {
    const float k0 = 0.7978845608028654f, k1 = 0.044715f;
    float inner = k0 * (x + k1 * x * x * x);
    return 0.5f * x * (1.f + tanhf(inner));
}

__global__ void __launch_bounds__(256) mod_kernel(const bf16* __restrict__ c, const bf16* __restrict__ w_mod) {
    __shared__ float sc[DM];
    __shared__ float part[32][65];
    int tid = threadIdx.x;
    for (int d = tid; d < DM; d += 256) {
        float cv = __bfloat162float(c[d]);
        sc[d] = bfr(cv / (1.f + expf(-cv)));
    }
    __syncthreads();
    int col0 = blockIdx.x * 64;
    int dg = tid >> 3, cg = tid & 7;
    float acc[8];
#pragma unroll
    for (int q = 0; q < 8; ++q) acc[q] = 0.f;
    for (int dd = 0; dd < 16; ++dd) {
        int d = dg * 16 + dd;
        uint4 v = *reinterpret_cast<const uint4*>(w_mod + (size_t)d * (6*DM) + col0 + cg * 8);
        const uint32_t* u = reinterpret_cast<const uint32_t*>(&v);
        float s = sc[d];
#pragma unroll
        for (int q = 0; q < 4; ++q) { float2 f = unpack_bf16(u[q]); acc[2*q] += s * f.x; acc[2*q+1] += s * f.y; }
    }
#pragma unroll
    for (int q = 0; q < 8; ++q) part[dg][cg*8+q] = acc[q];
    __syncthreads();
    if (tid < 64) {
        float s = 0.f;
        for (int g = 0; g < 32; ++g) s += part[g][tid];
        g_mod[col0 + tid] = bfr(s);
    }
    for (int idx = blockIdx.x * 256 + tid; idx < NSEG*MEMN*DM; idx += gridDim.x * 256) g_acc[idx] = 0ull;
}

__device__ __forceinline__ void ln_row16(float* x  ) {
    float s = 0.f;
#pragma unroll
    for (int i = 0; i < 16; ++i) s += x[i];
#pragma unroll
    for (int o = 16; o > 0; o >>= 1) s += __shfl_xor_sync(0xffffffffu, s, o);
    float mean = s * (1.f / DM);
    float q = 0.f;
#pragma unroll
    for (int i = 0; i < 16; ++i) { float d = x[i] - mean; q += d * d; }
#pragma unroll
    for (int o = 16; o > 0; o >>= 1) q += __shfl_xor_sync(0xffffffffu, q, o);
    float m = bfr(mean);
    float v = bfr(q * (1.f / DM));
    float den = bfr(sqrtf(bfr(v + 1e-5f)));
#pragma unroll
    for (int i = 0; i < 16; ++i) x[i] = bfr(bfr(x[i] - m) / den);
}
__device__ __forceinline__ void load_row16(const bf16* p, int lane, float* x) {
#pragma unroll
    for (int h = 0; h < 2; ++h) {
        uint4 v = *reinterpret_cast<const uint4*>(p + h * 256 + lane * 8);
        const uint32_t* u = reinterpret_cast<const uint32_t*>(&v);
#pragma unroll
        for (int q = 0; q < 4; ++q) { float2 f = unpack_bf16(u[q]); x[h*8+2*q] = f.x; x[h*8+2*q+1] = f.y; }
    }
}
__device__ __forceinline__ void store_row16(bf16* p, int lane, const float* x) {
#pragma unroll
    for (int h = 0; h < 2; ++h) {
        uint4 v; uint32_t* u = reinterpret_cast<uint32_t*>(&v);
#pragma unroll
        for (int q = 0; q < 4; ++q) u[q] = pack_bf16(x[h*8+2*q], x[h*8+2*q+1]);
        *reinterpret_cast<uint4*>(p + h * 256 + lane * 8) = v;
    }
}
__device__ __forceinline__ void modulate_row16(float* x, int lane, const float* shift, const float* scale) {
#pragma unroll
    for (int h = 0; h < 2; ++h)
#pragma unroll
        for (int q = 0; q < 8; ++q) {
            int col = h * 256 + lane * 8 + q;
            float t = bfr(x[h*8+q] * bfr(1.f + scale[col]));
            x[h*8+q] = bfr(t + shift[col]);
        }
}

__global__ void __launch_bounds__(256) ln1_kernel(const bf16* __restrict__ x) {
    int warp = (blockIdx.x * 256 + threadIdx.x) >> 5, lane = threadIdx.x & 31;
    if (warp >= S_LEN) return;
    float v[16];
    load_row16(x + (size_t)warp * DM, lane, v);
    ln_row16(v);
    modulate_row16(v, lane, g_mod + 0*DM, g_mod + 1*DM);
    store_row16(g_h1 + (size_t)warp * DM, lane, v);
}
__global__ void __launch_bounds__(256) ln2_kernel() {
    int warp = (blockIdx.x * 256 + threadIdx.x) >> 5, lane = threadIdx.x & 31;
    if (warp >= S_LEN) return;
    float v[16];
    load_row16(g_x2 + (size_t)warp * DM, lane, v);
    ln_row16(v);
    modulate_row16(v, lane, g_mod + 3*DM, g_mod + 4*DM);
    store_row16(g_h2 + (size_t)warp * DM, lane, v);
    ln_row16(v);
    store_row16(g_a1 + (size_t)warp * DM, lane, v);
}
__global__ void __launch_bounds__(256) ln3_kernel() {
    int warp = (blockIdx.x * 256 + threadIdx.x) >> 5, lane = threadIdx.x & 31;
    if (warp >= S_LEN) return;
    float v[16];
    load_row16(g_x1 + (size_t)warp * DM, lane, v);
    ln_row16(v);
    store_row16(g_a3 + (size_t)warp * DM, lane, v);
}

template <int BM, int BN, int WARPS_M, int WARPS_N, int STAGES, class P>
__global__ void __launch_bounds__(WARPS_M*WARPS_N*32) gemm_kernel(P p) {
    constexpr int BK = 32;
    constexpr int NT = WARPS_M * WARPS_N * 32;
    constexpr int LDA = BK + 8, LDB = BN + 8;
    constexpr int WM = BM / WARPS_M, WN = BN / WARPS_N;
    constexpr int MT = WM / 16, NTL = WN / 8;
    extern __shared__ __align__(16) unsigned char smem_raw[];
    bf16* sA = reinterpret_cast<bf16*>(smem_raw);
    bf16* sB = sA + STAGES * BM * LDA;

    const int tid = threadIdx.x, lane = tid & 31, warp = tid >> 5;
    const int wm = warp / WARPS_N, wn = warp % WARPS_N;
    const int m0 = blockIdx.x * BM, n0 = blockIdx.y * BN;
    const int KT = p.K / BK;

    auto load_stage = [&](int st, int kt) {
        for (int c = tid; c < BM * 4; c += NT) {
            int r = c >> 2, ch = c & 3;
            bool valid; const bf16* src = p.a_ptr(m0 + r, kt * BK + ch * 8, valid);
            cp_async16_zfill(smem_u32(sA + (st * BM + r) * LDA + ch * 8), src, valid);
        }
        for (int c = tid; c < BK * (BN / 8); c += NT) {
            int r = c / (BN / 8), ch = c % (BN / 8);
            bool valid = (n0 + ch * 8) < p.N;
            const bf16* src = p.b_ptr(kt * BK + r, valid ? (n0 + ch * 8) : 0);
            cp_async16_zfill(smem_u32(sB + (st * BK + r) * LDB + ch * 8), src, valid);
        }
    };

    float acc[MT][NTL][4];
#pragma unroll
    for (int i = 0; i < MT; ++i)
#pragma unroll
        for (int j = 0; j < NTL; ++j) { acc[i][j][0] = acc[i][j][1] = acc[i][j][2] = acc[i][j][3] = 0.f; }

#pragma unroll
    for (int s = 0; s < STAGES - 1; ++s) { if (s < KT) load_stage(s, s); cp_async_commit(); }

    for (int kt = 0; kt < KT; ++kt) {
        cp_async_wait<STAGES - 2>();
        __syncthreads();
        int nk = kt + STAGES - 1;
        if (nk < KT) load_stage(nk % STAGES, nk);
        cp_async_commit();
        const bf16* a_s = sA + (kt % STAGES) * BM * LDA;
        const bf16* b_s = sB + (kt % STAGES) * BK * LDB;
#pragma unroll
        for (int kk = 0; kk < 2; ++kk) {
            uint32_t af[MT][4], bfr_[NTL][2];
#pragma unroll
            for (int i = 0; i < MT; ++i) {
                int r = wm * WM + i * 16 + (lane & 7) + ((lane >> 3) & 1) * 8;
                int cidx = kk * 16 + (lane >> 4) * 8;
                ldsm_x4(af[i], smem_u32(a_s + r * LDA + cidx));
            }
#pragma unroll
            for (int j = 0; j < NTL; j += 2) {
                int r = kk * 16 + (lane & 7) + ((lane >> 3) & 1) * 8;
                int cidx = wn * WN + j * 8 + (lane >> 4) * 8;
                uint32_t t[4];
                ldsm_x4_t(t, smem_u32(b_s + r * LDB + cidx));
                bfr_[j][0] = t[0]; bfr_[j][1] = t[1]; bfr_[j+1][0] = t[2]; bfr_[j+1][1] = t[3];
            }
#pragma unroll
            for (int i = 0; i < MT; ++i)
#pragma unroll
                for (int j = 0; j < NTL; ++j) mma16816(acc[i][j], af[i], bfr_[j]);
        }
    }
    cp_async_wait<0>();
#pragma unroll
    for (int i = 0; i < MT; ++i)
#pragma unroll
        for (int j = 0; j < NTL; ++j) {
            int r = m0 + wm * WM + i * 16 + (lane >> 2);
            int c = n0 + wn * WN + j * 8 + (lane & 3) * 2;
            if (c < p.N) {
                p.epi(r, c, acc[i][j][0], acc[i][j][1]);
                p.epi(r + 8, c, acc[i][j][2], acc[i][j][3]);
            }
        }
}

#define WG_STAGES 4
__device__ __forceinline__ void mbar_wait_g(uint32_t mb, uint32_t parity) {
    uint32_t ok;
    do {
        asm volatile("{\n.reg .pred p;\nmbarrier.try_wait.parity.shared::cta.b64 p, [%1], %2;\nselp.u32 %0,1,0,p;\n}"
            : "=r"(ok) : "r"(mb), "r"(parity) : "memory");
    } while (!ok);
}
__device__ __forceinline__ void tma2d(uint32_t dst, const CUtensorMap* tm, uint32_t mb, int c0, int c1) {
    asm volatile("cp.async.bulk.tensor.2d.shared::cluster.global.mbarrier::complete_tx::bytes [%0], [%1, {%3, %4}], [%2];"
        :: "r"(dst), "l"(tm), "r"(mb), "r"(c0), "r"(c1) : "memory");
}
template <class P>
__global__ void __launch_bounds__(288, 1) wgemm_kernel(const __grid_constant__ CUtensorMap tA, const __grid_constant__ CUtensorMap tB0,
        const __grid_constant__ CUtensorMap tB1, const __grid_constant__ CUtensorMap tB2, P p) {
    extern __shared__ unsigned char smem_raw[];
    const uint32_t sbase = (smem_u32(smem_raw) + 1023) & ~1023u;
    __shared__ __align__(8) unsigned long long bars[2 * WG_STAGES];
    const int tid = threadIdx.x, warp = tid >> 5, lane = tid & 31;
    const int m0 = blockIdx.x * 128, n0 = blockIdx.y * 128;
    const int KT = (p.K + 63) / 64;
    if (tid == 0) {
        for (int i = 0; i < WG_STAGES; ++i) {
            asm volatile("mbarrier.init.shared::cta.b64 [%0], 1;" :: "r"(smem_u32(&bars[i])));
            asm volatile("mbarrier.init.shared::cta.b64 [%0], 2;" :: "r"(smem_u32(&bars[WG_STAGES + i])));
        }
        asm volatile("fence.mbarrier_init.release.cluster;" ::: "memory");
    }
    __syncthreads();
    if (warp == 8) {
        if (lane == 0) {
            int bsel = p.bsel(n0);
            const CUtensorMap* tb = bsel == 0 ? &tB0 : (bsel == 1 ? &tB1 : &tB2);
            int nb = p.bcol(n0);
            for (int kt = 0; kt < KT; ++kt) {
                int st = kt % WG_STAGES;
                if (kt >= WG_STAGES) mbar_wait_g(smem_u32(&bars[WG_STAGES + st]), ((kt / WG_STAGES) - 1) & 1);
                uint32_t full = smem_u32(&bars[st]);
                asm volatile("mbarrier.arrive.expect_tx.shared::cta.b64 _, [%0], %1;" :: "r"(full), "r"(32768) : "memory");
                uint32_t sa = sbase + st * 32768, sb = sa + 16384;
                tma2d(sa, &tA, full, kt * 64, m0 + p.arow_shift(kt * 64));
                tma2d(sb, tb, full, nb, kt * 64);
                tma2d(sb + 8192, tb, full, nb + 64, kt * 64);
            }
        }
        return;
    }
    const int wg = warp >> 2;
    float acc[64];
#pragma unroll
    for (int i = 0; i < 64; ++i) acc[i] = 0.f;
    for (int kt = 0; kt < KT; ++kt) {
        int st = kt % WG_STAGES;
        mbar_wait_g(smem_u32(&bars[st]), (kt / WG_STAGES) & 1);
        uint32_t sa = sbase + st * 32768 + wg * 8192, sb = sbase + st * 32768 + 16384;
        uint64_t da = (uint64_t)((sa & 0x3FFFF) >> 4) | ((uint64_t)1 << 16) | ((uint64_t)(1024 >> 4) << 32) | ((uint64_t)1 << 62);
        uint64_t db = (uint64_t)((sb & 0x3FFFF) >> 4) | ((uint64_t)(8192 >> 4) << 16) | ((uint64_t)(1024 >> 4) << 32) | ((uint64_t)1 << 62);
        asm volatile("wgmma.fence.sync.aligned;" ::: "memory");
#pragma unroll
        for (int kk = 0; kk < 4; ++kk) {
            asm volatile("{\n.reg .pred p;\nsetp.ne.b32 p, 1, 0;\n"
                "wgmma.mma_async.sync.aligned.m64n128k16.f32.bf16.bf16 "
                "{%0,%1,%2,%3,%4,%5,%6,%7,%8,%9,%10,%11,%12,%13,%14,%15,%16,%17,%18,%19,%20,%21,%22,%23,%24,%25,%26,%27,%28,%29,%30,%31,"
                "%32,%33,%34,%35,%36,%37,%38,%39,%40,%41,%42,%43,%44,%45,%46,%47,%48,%49,%50,%51,%52,%53,%54,%55,%56,%57,%58,%59,%60,%61,%62,%63},"
                " %64, %65, p, 1, 1, 0, 1;\n}"
                : "+f"(acc[0]),"+f"(acc[1]),"+f"(acc[2]),"+f"(acc[3]),"+f"(acc[4]),"+f"(acc[5]),"+f"(acc[6]),"+f"(acc[7]),
                  "+f"(acc[8]),"+f"(acc[9]),"+f"(acc[10]),"+f"(acc[11]),"+f"(acc[12]),"+f"(acc[13]),"+f"(acc[14]),"+f"(acc[15]),
                  "+f"(acc[16]),"+f"(acc[17]),"+f"(acc[18]),"+f"(acc[19]),"+f"(acc[20]),"+f"(acc[21]),"+f"(acc[22]),"+f"(acc[23]),
                  "+f"(acc[24]),"+f"(acc[25]),"+f"(acc[26]),"+f"(acc[27]),"+f"(acc[28]),"+f"(acc[29]),"+f"(acc[30]),"+f"(acc[31]),
                  "+f"(acc[32]),"+f"(acc[33]),"+f"(acc[34]),"+f"(acc[35]),"+f"(acc[36]),"+f"(acc[37]),"+f"(acc[38]),"+f"(acc[39]),
                  "+f"(acc[40]),"+f"(acc[41]),"+f"(acc[42]),"+f"(acc[43]),"+f"(acc[44]),"+f"(acc[45]),"+f"(acc[46]),"+f"(acc[47]),
                  "+f"(acc[48]),"+f"(acc[49]),"+f"(acc[50]),"+f"(acc[51]),"+f"(acc[52]),"+f"(acc[53]),"+f"(acc[54]),"+f"(acc[55]),
                  "+f"(acc[56]),"+f"(acc[57]),"+f"(acc[58]),"+f"(acc[59]),"+f"(acc[60]),"+f"(acc[61]),"+f"(acc[62]),"+f"(acc[63])
                : "l"(da + (uint64_t)(kk * 2)), "l"(db + (uint64_t)(kk * 128)));
        }
        asm volatile("wgmma.commit_group.sync.aligned;" ::: "memory");
        asm volatile("wgmma.wait_group.sync.aligned 0;" ::: "memory");
        if ((tid & 127) == 0) asm volatile("mbarrier.arrive.shared::cta.b64 _, [%0];" :: "r"(smem_u32(&bars[WG_STAGES + st])) : "memory");
    }
    const int r0 = m0 + wg * 64 + (warp & 3) * 16 + (lane >> 2);
#pragma unroll
    for (int j = 0; j < 16; ++j) {
        int c = n0 + j * 8 + (lane & 3) * 2;
        if (c < p.N) { p.epi(r0, c, acc[4*j], acc[4*j+1]); p.epi(r0 + 8, c, acc[4*j+2], acc[4*j+3]); }
    }
}

struct PQKV {
    const bf16 *wq, *wk, *wv; int N, K;
    __device__ int bsel(int n0) const { return n0 / HD; }
    __device__ int bcol(int n0) const { return n0 % HD; }
    __device__ int arow_shift(int) const { return 0; }
    __device__ const bf16* a_ptr(int r, int k, bool& valid) const { valid = true; return g_h1 + (size_t)r * DM + k; }
    __device__ const bf16* b_ptr(int k, int n) const {
        int sel = n / HD; const bf16* w = sel == 0 ? wq : (sel == 1 ? wk : wv);
        return w + (size_t)k * HD + (n - sel * HD);
    }
    __device__ void epi(int r, int c, float v0, float v1) const {
        *reinterpret_cast<uint32_t*>(g_qkv + (size_t)r * (3*HD) + c) = pack_bf16(v0, v1);
    }
};
struct POut {
    const bf16 *wo, *x; int N, K;
    __device__ int bsel(int) const { return 0; }
    __device__ int bcol(int n0) const { return n0; }
    __device__ int arow_shift(int) const { return 0; }
    __device__ const bf16* a_ptr(int r, int k, bool& valid) const { valid = true; return g_o + (size_t)r * HD + k; }
    __device__ const bf16* b_ptr(int k, int n) const { return wo + (size_t)k * DM + n; }
    __device__ void epi(int r, int c, float v0, float v1) const {
        float2 xv = unpack_bf16(*reinterpret_cast<const uint32_t*>(x + (size_t)r * DM + c));
        float ga0 = g_mod[2*DM + c], ga1 = g_mod[2*DM + c + 1];
        float o0 = bfr(xv.x + bfr(ga0 * bfr(v0)));
        float o1 = bfr(xv.y + bfr(ga1 * bfr(v1)));
        *reinterpret_cast<uint32_t*>(g_x2 + (size_t)r * DM + c) = pack_bf16(o0, o1);
    }
};
struct PW1 {
    const bf16 *w; int N, K;
    __device__ int bsel(int) const { return 0; }
    __device__ int bcol(int n0) const { return n0; }
    __device__ int arow_shift(int) const { return 0; }
    __device__ const bf16* a_ptr(int r, int k, bool& valid) const { valid = true; return g_a1 + (size_t)r * DM + k; }
    __device__ const bf16* b_ptr(int k, int n) const { return w + (size_t)k * DM + n; }
    __device__ void epi(int r, int c, float v0, float v1) const {
        *reinterpret_cast<uint32_t*>(g_g + (size_t)r * DM + c) = pack_bf16(gelu_tanh(bfr(v0)), gelu_tanh(bfr(v1)));
    }
};
struct PW2 {
    const bf16 *w; int N, K;
    __device__ int bsel(int) const { return 0; }
    __device__ int bcol(int n0) const { return n0; }
    __device__ int arow_shift(int k) const { int q = k >> 7; return q == 0 ? -1 : (q == 1 ? 1 : (q == 2 ? -2 : 2)); }
    __device__ const bf16* a_ptr(int r, int k, bool& valid) const {
        int q = k >> 7;
        int src = r + (q == 0 ? -1 : (q == 1 ? 1 : (q == 2 ? -2 : 2)));
        valid = (src >= 0) && (src < S_LEN);
        return g_g + (size_t)(valid ? src : 0) * DM + k;
    }
    __device__ const bf16* b_ptr(int k, int n) const { return w + (size_t)k * DM + n; }
    __device__ void epi(int r, int c, float v0, float v1) const {
        float2 hv = unpack_bf16(*reinterpret_cast<const uint32_t*>(g_h2 + (size_t)r * DM + c));
        *reinterpret_cast<uint32_t*>(g_x1 + (size_t)r * DM + c) = pack_bf16(hv.x + bfr(v0), hv.y + bfr(v1));
    }
};
struct PW3 {
    const bf16 *w; int N, K;
    __device__ int bsel(int) const { return 0; }
    __device__ int bcol(int n0) const { return n0; }
    __device__ int arow_shift(int) const { return 0; }
    __device__ const bf16* a_ptr(int r, int k, bool& valid) const { valid = true; return g_a3 + (size_t)r * DM + k; }
    __device__ const bf16* b_ptr(int k, int n) const { return w + (size_t)k * FF + n; }
    __device__ void epi(int r, int c, float v0, float v1) const {
        *reinterpret_cast<uint32_t*>(g_u + (size_t)r * FF + c) = pack_bf16(gelu_tanh(bfr(v0)), gelu_tanh(bfr(v1)));
    }
};
struct PW4 {
    const bf16 *w; bf16* out; int N, K;
    __device__ int bsel(int) const { return 0; }
    __device__ int bcol(int n0) const { return n0; }
    __device__ int arow_shift(int) const { return 0; }
    __device__ const bf16* a_ptr(int r, int k, bool& valid) const { valid = true; return g_u + (size_t)r * FF + k; }
    __device__ const bf16* b_ptr(int k, int n) const { return w + (size_t)k * DM + n; }
    __device__ void epi(int r, int c, float v0, float v1) const {
        float2 x1 = unpack_bf16(*reinterpret_cast<const uint32_t*>(g_x1 + (size_t)r * DM + c));
        float2 x2 = unpack_bf16(*reinterpret_cast<const uint32_t*>(g_x2 + (size_t)r * DM + c));
        float gb0 = g_mod[5*DM + c], gb1 = g_mod[5*DM + c + 1];
        float b0 = bfr(x1.x + bfr(v0)), b1 = bfr(x1.y + bfr(v1));
        float o0 = bfr(x2.x + bfr(gb0 * b0)), o1 = bfr(x2.y + bfr(gb1 * b1));
        *reinterpret_cast<uint32_t*>(out + (size_t)r * DM + c) = pack_bf16(o0, o1);
    }
};

#define CH_LDM   (DM + 8)
#define CH_LDW   (64 + 8)
#define CH_LDO   (256 + 8)
#define CH_LDP   (48 + 8)
#define CH_LDOS  (DH + 8)
struct ChainSmem {
    bf16  mem_s[MEMN * CH_LDM];
    bf16  wv_s[DM * CH_LDW];
    bf16  wo_s[DH * CH_LDO];
    bf16  q_s[MEMN * CH_LDW];
    bf16  k_s[2][48 * CH_LDW];
    bf16  v_s[2][48 * CH_LDW];
    float xs[2][40 * 8];
    bf16  p_s[MEMN * CH_LDP];
    bf16  o_s[MEMN * CH_LDOS];
    unsigned long long mbar[3];
};
#define FIX_SCALE 1073741824.0f
#define POLL_DELAY 1100
#define PROF_T(idx) do { } while (0)

__device__ __forceinline__ void mbar_wait(uint32_t mb, uint32_t parity) {
    uint32_t ok; int it = 0;
    do {
        asm volatile("{\n.reg .pred p;\nmbarrier.try_wait.parity.shared::cta.b64 p, [%1], %2;\nselp.u32 %0,1,0,p;\n}"
            : "=r"(ok) : "r"(mb), "r"(parity) : "memory");
        if (++it > (1 << 24)) asm volatile("trap;");
    } while (!ok);
}

__global__ void __cluster_dims__(2,1,1) __launch_bounds__(256, 1)
chain_kernel(const bf16* __restrict__ mem0, const bf16* __restrict__ Wq, const bf16* __restrict__ Wk,
             const bf16* __restrict__ Wv, const bf16* __restrict__ Wo) {
    extern __shared__ __align__(16) unsigned char smem_raw[];
    ChainSmem& sm = *reinterpret_cast<ChainSmem*>(smem_raw);
    const int tid = threadIdx.x, lane = tid & 31, warp = tid >> 5;
    const int h = blockIdx.x >> 1, ih = blockIdx.x & 1;
    const int g = lane >> 2, t4 = lane & 3;
    const int ecol0 = h * DH + ih * 64;

    uint32_t wqk[32][4];
    {
        for (int sel = 0; sel < 2; ++sel) {
            const bf16* W = sel == 0 ? Wq : Wk;
            __syncthreads();
            for (int c = tid; c < DM * 8; c += 256) {
                int r = c >> 3, ch = c & 7;
                cp_async16(smem_u32(sm.wv_s + r * CH_LDW + ch * 8), W + (size_t)r * HD + ecol0 + ch * 8);
            }
            cp_async_commit(); cp_async_wait<0>();
            __syncthreads();
            if ((warp >> 2) == sel) {
                int et = warp & 3;
#pragma unroll
                for (int kk = 0; kk < 32; ++kk) {
                    int r = kk * 16 + (lane & 7) + (lane >> 4) * 8;
                    int cidx = et * 16 + ((lane >> 3) & 1) * 8;
                    ldsm_x4_t(wqk[kk], smem_u32(sm.wv_s + r * CH_LDW + cidx));
                }
            }
        }
        __syncthreads();
    }
    for (int c = tid; c < DM * 8; c += 256) {
        int r = c >> 3, ch = c & 7;
        cp_async16(smem_u32(sm.wv_s + r * CH_LDW + ch * 8), Wv + (size_t)r * HD + ecol0 + ch * 8);
    }
    for (int c = tid; c < DH * 32; c += 256) {
        int r = c >> 5, ch = c & 31;
        cp_async16(smem_u32(sm.wo_s + r * CH_LDO + ch * 8), Wo + (size_t)(h * DH + r) * DM + ih * 256 + ch * 8);
    }
    for (int c = tid; c < MEMN * 64; c += 256) {
        int r = c >> 6, ch = c & 63;
        cp_async16(smem_u32(sm.mem_s + r * CH_LDM + ch * 8), mem0 + r * DM + ch * 8);
    }
    auto prefetch_kv = [&](int seg, int buf) {
        for (int c = tid; c < 2 * SEG * 8; c += 256) {
            int which = c >> 8, r = (c >> 3) & 31, ch = c & 7;
            const bf16* src = g_qkv + (size_t)(seg * SEG + r) * (3*HD) + (1 + which) * HD + ecol0 + ch * 8;
            bf16* dst = (which == 0 ? sm.k_s[buf] : sm.v_s[buf]) + (8 + r) * CH_LDW + ch * 8;
            cp_async16(smem_u32(dst), src);
        }
    };
    prefetch_kv(0, 0);
    cp_async_commit();
    if (tid < 8)
        asm volatile("prefetch.global.L2 [%0];" :: "l"(g_acc + (size_t)(tid >> 2) * (MEMN * DM) + (blockIdx.x * 4 + (tid & 3)) * 16));
    for (int c = tid; c < 2 * 2 * 8 * CH_LDW; c += 256) {
        int b = c / (2 * 8 * CH_LDW), rem = c % (2 * 8 * CH_LDW), which = rem / (8 * CH_LDW), off = rem % (8 * CH_LDW);
        (which == 0 ? sm.k_s[b] : sm.v_s[b])[40 * CH_LDW + off] = __float2bfloat16(0.f);
    }
    for (int c = tid; c < MEMN * CH_LDP; c += 256) sm.p_s[c] = __float2bfloat16(0.f);
    const uint32_t mb1 = smem_u32(&sm.mbar[0]), mb2 = smem_u32(&sm.mbar[1]), mb3 = smem_u32(&sm.mbar[2]);
    if (tid == 0) {
        asm volatile("mbarrier.init.shared::cta.b64 [%0], 1;" :: "r"(mb1));
        asm volatile("mbarrier.init.shared::cta.b64 [%0], 1;" :: "r"(mb2));
        asm volatile("mbarrier.init.shared::cta.b64 [%0], 1;" :: "r"(mb3));
        asm volatile("fence.mbarrier_init.release.cluster;" ::: "memory");
    }
    cp_async_wait<0>();
    asm volatile("barrier.cluster.arrive.release.aligned;\nbarrier.cluster.wait.acquire.aligned;" ::: "memory");
    uint32_t peer_xs, peer_os, peer_mb1, peer_mb2, peer_mb3, peer_mem;
    asm volatile("mapa.shared::cluster.u32 %0, %1, %2;" : "=r"(peer_mb3) : "r"(mb3), "r"(ih ^ 1));
    asm volatile("mapa.shared::cluster.u32 %0, %1, %2;" : "=r"(peer_mem) : "r"(smem_u32(sm.mem_s)), "r"(ih ^ 1));
    asm volatile("mapa.shared::cluster.u32 %0, %1, %2;" : "=r"(peer_xs)  : "r"(smem_u32(sm.xs[ih])), "r"(ih ^ 1));
    asm volatile("mapa.shared::cluster.u32 %0, %1, %2;" : "=r"(peer_os)  : "r"(smem_u32(sm.o_s)), "r"(ih ^ 1));
    asm volatile("mapa.shared::cluster.u32 %0, %1, %2;" : "=r"(peer_mb1) : "r"(mb1), "r"(ih ^ 1));
    asm volatile("mapa.shared::cluster.u32 %0, %1, %2;" : "=r"(peer_mb2) : "r"(mb2), "r"(ih ^ 1));
    const uint32_t own_xs = smem_u32(sm.xs[ih]), own_os = smem_u32(sm.o_s);

    const float scale = 0.08838834764831845f;

    for (int s = 0; s < NSEG; ++s) {
        const int buf = s & 1;
        const bool last = (s == NSEG - 1);
        if (tid == 0 && !last) {
            asm volatile("mbarrier.arrive.expect_tx.shared::cta.b64 _, [%0], %1;" :: "r"(mb1), "r"(2 * 40 * 8 * 4) : "memory");
            asm volatile("mbarrier.arrive.expect_tx.shared::cta.b64 _, [%0], %1;" :: "r"(mb2), "r"(MEMN * DH * 2) : "memory");
            asm volatile("mbarrier.arrive.expect_tx.shared::cta.b64 _, [%0], %1;" :: "r"(mb3), "r"(4 * DM * 2) : "memory");
        }
        PROF_T(11);
        if (tid < 4 && s + 2 < NSEG)
            asm volatile("prefetch.global.L2 [%0];" :: "l"(g_acc + (size_t)(s + 2) * (MEMN * DM) + (blockIdx.x * 4 + tid) * 16));
        if (!last) prefetch_kv(s + 1, buf ^ 1);
        cp_async_commit();
        PROF_T(12);

        {
            float c4[4][4];
#pragma unroll
            for (int i = 0; i < 4; ++i) { c4[i][0] = c4[i][1] = c4[i][2] = c4[i][3] = 0.f; }
            const uint32_t mem_addr = smem_u32(sm.mem_s + (lane & 7) * CH_LDM + (lane >> 3) * 8);
            uint32_t b4[2][4];
            ldsm_x4(b4[0], mem_addr);
#pragma unroll
            for (int kk = 0; kk < 32; kk += 2) {
                if (kk + 2 < 32) ldsm_x4(b4[((kk >> 1) + 1) & 1], mem_addr + (kk + 2) * 32);
                mma16816(c4[kk & 3], wqk[kk], b4[(kk >> 1) & 1]);
                mma16816(c4[(kk + 1) & 3], wqk[kk + 1], b4[(kk >> 1) & 1] + 2);
            }
            float r0 = c4[0][0] + c4[1][0] + c4[2][0] + c4[3][0];
            float r1 = c4[0][1] + c4[1][1] + c4[2][1] + c4[3][1];
            float r2 = c4[0][2] + c4[1][2] + c4[2][2] + c4[3][2];
            float r3 = c4[0][3] + c4[1][3] + c4[2][3] + c4[3][3];
            int e0 = (warp & 3) * 16 + g;
            bf16* dst = (warp < 4) ? sm.q_s : sm.k_s[buf];
            dst[(2*t4)   * CH_LDW + e0]     = __float2bfloat16_rn(r0);
            dst[(2*t4+1) * CH_LDW + e0]     = __float2bfloat16_rn(r1);
            dst[(2*t4)   * CH_LDW + e0 + 8] = __float2bfloat16_rn(r2);
            dst[(2*t4+1) * CH_LDW + e0 + 8] = __float2bfloat16_rn(r3);
        }
        PROF_T(0);
        cp_async_wait<1>();
        __syncthreads();
        PROF_T(1);

        if (warp >= 4) {
            int et = warp - 4;
            float c2[2][4];
#pragma unroll
            for (int i = 0; i < 2; ++i) { c2[i][0] = c2[i][1] = c2[i][2] = c2[i][3] = 0.f; }
            const uint32_t mem_addr = smem_u32(sm.mem_s + (lane & 7) * CH_LDM + (lane >> 3) * 8);
            const uint32_t wv_addr = smem_u32(sm.wv_s + ((lane & 7) + (lane >> 4) * 8) * CH_LDW + et * 16 + ((lane >> 3) & 1) * 8);
            uint32_t b4[2][4], a0[2][4], a1[2][4];
            ldsm_x4(b4[0], mem_addr);
            ldsm_x4_t(a0[0], wv_addr);
            ldsm_x4_t(a1[0], wv_addr + 16 * CH_LDW * 2);
#pragma unroll
            for (int kk = 0; kk < 32; kk += 2) {
                const int cur = (kk >> 1) & 1, nxt = cur ^ 1;
                if (kk + 2 < 32) {
                    ldsm_x4(b4[nxt], mem_addr + (kk + 2) * 32);
                    ldsm_x4_t(a0[nxt], wv_addr + (kk + 2) * 16 * CH_LDW * 2);
                    ldsm_x4_t(a1[nxt], wv_addr + (kk + 3) * 16 * CH_LDW * 2);
                }
                mma16816(c2[0], a0[cur], b4[cur]);
                mma16816(c2[1], a1[cur], b4[cur] + 2);
            }
            int e0 = et * 16 + g;
            bf16* dst = sm.v_s[buf];
            dst[(2*t4)   * CH_LDW + e0]     = __float2bfloat16_rn(c2[0][0] + c2[1][0]);
            dst[(2*t4+1) * CH_LDW + e0]     = __float2bfloat16_rn(c2[0][1] + c2[1][1]);
            dst[(2*t4)   * CH_LDW + e0 + 8] = __float2bfloat16_rn(c2[0][2] + c2[1][2]);
            dst[(2*t4+1) * CH_LDW + e0 + 8] = __float2bfloat16_rn(c2[0][3] + c2[1][3]);
        } else if (!last) {
            if (warp < 3) {
                float c[4] = {0.f, 0.f, 0.f, 0.f};
#pragma unroll
                for (int kk = 0; kk < 4; kk += 2) {
                    uint32_t b4[4], a0[4], a1[4];
                    ldsm_x4(b4, smem_u32(sm.q_s + (lane & 7) * CH_LDW + kk * 16 + (lane >> 3) * 8));
                    int r = warp * 16 + (lane & 7) + ((lane >> 3) & 1) * 8;
                    ldsm_x4(a0, smem_u32(sm.k_s[buf] + r * CH_LDW + kk * 16 + (lane >> 4) * 8));
                    ldsm_x4(a1, smem_u32(sm.k_s[buf] + r * CH_LDW + (kk + 1) * 16 + (lane >> 4) * 8));
                    mma16816(c, a0, b4);
                    mma16816(c, a1, b4 + 2);
                }
                int key = warp * 16 + g;
                uint32_t off = (key * 8 + 2 * t4) * 4;
                asm volatile("st.async.shared::cluster.mbarrier::complete_tx::bytes.v2.f32 [%0], {%1,%2}, [%3];"
                    :: "r"(own_xs + off), "f"(c[0]), "f"(c[1]), "r"(mb1) : "memory");
                asm volatile("st.async.shared::cluster.mbarrier::complete_tx::bytes.v2.f32 [%0], {%1,%2}, [%3];"
                    :: "r"(peer_xs + off), "f"(c[0]), "f"(c[1]), "r"(peer_mb1) : "memory");
                if (warp < 2) {
                    off += 8 * 8 * 4;
                    asm volatile("st.async.shared::cluster.mbarrier::complete_tx::bytes.v2.f32 [%0], {%1,%2}, [%3];"
                        :: "r"(own_xs + off), "f"(c[2]), "f"(c[3]), "r"(mb1) : "memory");
                    asm volatile("st.async.shared::cluster.mbarrier::complete_tx::bytes.v2.f32 [%0], {%1,%2}, [%3];"
                        :: "r"(peer_xs + off), "f"(c[2]), "f"(c[3]), "r"(peer_mb1) : "memory");
                }
            }
            PROF_T(2);
            mbar_wait(mb1, s & 1);
            PROF_T(3);
            {
                int row = warp * 2 + (lane >> 4), l = lane & 15;
                float sc[3]; float mx = -3.0e38f;
#pragma unroll
                for (int q = 0; q < 3; ++q) {
                    int key = l + q * 16;
                    if (key < 40) {
                        float v = sm.xs[0][key * 8 + row] + sm.xs[1][key * 8 + row];
                        v = bfr(bfr(v) * scale);
                        sc[q] = v; mx = fmaxf(mx, v);
                    } else sc[q] = 0.f;
                }
#pragma unroll
                for (int o = 8; o > 0; o >>= 1) mx = fmaxf(mx, __shfl_xor_sync(0xffffffffu, mx, o));
                float sum = 0.f;
#pragma unroll
                for (int q = 0; q < 3; ++q) { int key = l + q * 16; if (key < 40) { sc[q] = expf(sc[q] - mx); sum += sc[q]; } }
#pragma unroll
                for (int o = 8; o > 0; o >>= 1) sum += __shfl_xor_sync(0xffffffffu, sum, o);
                float inv = 1.f / sum;
#pragma unroll
                for (int q = 0; q < 3; ++q) { int key = l + q * 16; if (key < 40) sm.p_s[row * CH_LDP + key] = __float2bfloat16_rn(sc[q] * inv); }
            }
        }
        PROF_T(4);
        __syncthreads();
        PROF_T(5);
        if (warp >= 4) {
            int c = tid - 128;
            int which = c >> 6, r = (c >> 3) & 7, ch = c & 7;
            const bf16* src = (which == 0 ? sm.k_s[buf] : sm.v_s[buf]) + r * CH_LDW + ch * 8;
            bf16* dst = (which == 0 ? g_km : g_vm) + (size_t)(s * MEMN + r) * HD + ecol0 + ch * 8;
            *reinterpret_cast<uint4*>(dst) = *reinterpret_cast<const uint4*>(src);
        }
        if (last) break;

        if (warp < 4) {
            float c[4] = {0.f, 0.f, 0.f, 0.f};
#pragma unroll
            for (int kk = 0; kk < 3; ++kk) {
                uint32_t a[4], b2[2];
                int r = kk * 16 + (lane & 7) + (lane >> 4) * 8;
                int cidx = warp * 16 + ((lane >> 3) & 1) * 8;
                ldsm_x4_t(a, smem_u32(sm.v_s[buf] + r * CH_LDW + cidx));
                ldsm_x2(b2, smem_u32(sm.p_s + (lane & 7) * CH_LDP + kk * 16 + ((lane >> 3) & 1) * 8));
                mma16816(c, a, b2);
            }
            uint32_t lo = pack_bf16(c[0], c[1]), hi = pack_bf16(c[2], c[3]);
            uint32_t tlo, thi;
            asm volatile("movmatrix.sync.aligned.m8n8.trans.b16 %0, %1;" : "=r"(tlo) : "r"(lo));
            asm volatile("movmatrix.sync.aligned.m8n8.trans.b16 %0, %1;" : "=r"(thi) : "r"(hi));
            uint32_t off = (g * CH_LDOS + ih * 64 + warp * 16 + 2 * t4) * 2;
            asm volatile("st.async.shared::cluster.mbarrier::complete_tx::bytes.b32 [%0], %1, [%2];" :: "r"(own_os + off), "r"(tlo), "r"(mb2) : "memory");
            asm volatile("st.async.shared::cluster.mbarrier::complete_tx::bytes.b32 [%0], %1, [%2];" :: "r"(own_os + off + 16), "r"(thi), "r"(mb2) : "memory");
            asm volatile("st.async.shared::cluster.mbarrier::complete_tx::bytes.b32 [%0], %1, [%2];" :: "r"(peer_os + off), "r"(tlo), "r"(peer_mb2) : "memory");
            asm volatile("st.async.shared::cluster.mbarrier::complete_tx::bytes.b32 [%0], %1, [%2];" :: "r"(peer_os + off + 16), "r"(thi), "r"(peer_mb2) : "memory");
        }
        PROF_T(6);
        mbar_wait(mb2, s & 1);
        PROF_T(7);

        unsigned long long* acc = g_acc + (size_t)s * (MEMN * DM);
        {
            uint32_t ob[4][4];
#pragma unroll
            for (int kk = 0; kk < 4; ++kk)
                ldsm_x4(ob[kk], smem_u32(sm.o_s + (lane & 7) * CH_LDOS + kk * 32 + (lane >> 3) * 8));
            const uint32_t wo_addr = smem_u32(sm.wo_s + ((lane & 7) + (lane >> 4) * 8) * CH_LDO + warp * 32 + ((lane >> 3) & 1) * 8);
            uint32_t wa[2][8][4];
#pragma unroll
            for (int kk = 0; kk < 8; ++kk) ldsm_x4_t(wa[0][kk], wo_addr + kk * 16 * CH_LDO * 2);
#pragma unroll
            for (int mt = 0; mt < 2; ++mt) {
                float c[4] = {0.f, 0.f, 0.f, 0.f}, c1[4] = {0.f, 0.f, 0.f, 0.f};
                int mtile = warp * 2 + mt;
                if (mt == 0) {
#pragma unroll
                    for (int kk = 0; kk < 8; ++kk) ldsm_x4_t(wa[1][kk], wo_addr + 32 + kk * 16 * CH_LDO * 2);
                }
#pragma unroll
                for (int kk = 0; kk < 8; kk += 2) {
                    mma16816(c,  wa[mt][kk],     ob[kk >> 1]);
                    mma16816(c1, wa[mt][kk + 1], ob[kk >> 1] + 2);
                }
#pragma unroll
                for (int q = 0; q < 4; ++q) c[q] += c1[q];
                int dcol = ih * 256 + mtile * 16 + g;
#pragma unroll
                for (int q = 0; q < 4; ++q) {
                    int d = dcol + (q >> 1) * 8, n = 2 * t4 + (q & 1);
                    long long fx = __float2ll_rn(c[q] * FIX_SCALE);
                    unsigned long long w = (1ull << 56) + (unsigned long long)fx;
                    asm volatile("red.relaxed.gpu.global.add.u64 [%0], %1;" :: "l"(acc + n * DM + d), "l"(w) : "memory");
                }
            }
        }
        PROF_T(8);
        {
            { long long t0 = clock64(); while (clock64() - t0 < POLL_DELAY) { } }
            unsigned long long w[8];
            const unsigned long long* accp = acc + ih * 4 * DM;
            int it = 0;
            for (;;) {
#pragma unroll
                for (int q = 0; q < 4; ++q)
                    asm volatile("ld.relaxed.gpu.global.v2.u64 {%0,%1}, [%2];" : "=l"(w[2*q]), "=l"(w[2*q+1]) : "l"(accp + (q * 256 + tid) * 2) : "memory");
                bool ok = true;
#pragma unroll
                for (int q = 0; q < 8; ++q) {
                    long long sv = (long long)(w[q] << 8) >> 8;
                    ok = ok && (((w[q] - (unsigned long long)sv) >> 56) == (unsigned long long)NH);
                }
                if (ok) break;
                if (++it > (1 << 22)) asm volatile("trap;");
            }
#pragma unroll
            for (int q = 0; q < 4; ++q) {
                float v0 = (float)((long long)(w[2*q] << 8) >> 8) * (1.f / FIX_SCALE);
                float v1 = (float)((long long)(w[2*q+1] << 8) >> 8) * (1.f / FIX_SCALE);
                uint32_t pk = pack_bf16(v0, v1);
                uint32_t off = ((ih * 4 + q) * CH_LDM + 2 * tid) * 2;
                *reinterpret_cast<uint32_t*>(reinterpret_cast<unsigned char*>(sm.mem_s) + off) = pk;
                asm volatile("st.async.shared::cluster.mbarrier::complete_tx::bytes.b32 [%0], %1, [%2];" :: "r"(peer_mem + off), "r"(pk), "r"(peer_mb3) : "memory");
            }
            mbar_wait(mb3, s & 1);
        }
        PROF_T(9);
        __syncthreads();
        PROF_T(10);
    }
    asm volatile("barrier.cluster.arrive.release.aligned;\nbarrier.cluster.wait.acquire.aligned;" ::: "memory");
}

#define TA_LD (DH + 8)
__global__ void __launch_bounds__(128) tok_attn_kernel() {
    __shared__ __align__(16) bf16 q_s[SEG * TA_LD];
    __shared__ __align__(16) bf16 k_s[48 * TA_LD];
    __shared__ __align__(16) bf16 v_s[48 * TA_LD];
    __shared__ __align__(16) bf16 p_s[SEG * CH_LDP];
    const int seg = blockIdx.x / NH, h = blockIdx.x % NH;
    const int tid = threadIdx.x, lane = tid & 31, warp = tid >> 5;
    const int g = lane >> 2, t4 = lane & 3;
    for (int c = tid; c < SEG * 16; c += 128) {
        int r = c >> 4, ch = c & 15;
        const bf16* base = g_qkv + (size_t)(seg * SEG + r) * (3*HD) + h * DH + ch * 8;
        cp_async16(smem_u32(q_s + r * TA_LD + ch * 8), base);
        cp_async16(smem_u32(k_s + (8 + r) * TA_LD + ch * 8), base + HD);
        cp_async16(smem_u32(v_s + (8 + r) * TA_LD + ch * 8), base + 2*HD);
    }
    for (int c = tid; c < MEMN * 16; c += 128) {
        int r = c >> 4, ch = c & 15;
        size_t off = (size_t)(seg * MEMN + r) * HD + h * DH + ch * 8;
        cp_async16(smem_u32(k_s + r * TA_LD + ch * 8), g_km + off);
        cp_async16(smem_u32(v_s + r * TA_LD + ch * 8), g_vm + off);
    }
    cp_async_commit();
    for (int c = tid; c < 8 * TA_LD; c += 128) { k_s[40 * TA_LD + c] = __float2bfloat16(0.f); v_s[40 * TA_LD + c] = __float2bfloat16(0.f); }
    cp_async_wait<0>();
    __syncthreads();
    const float scale = 0.08838834764831845f;
    {
        int mt = warp & 1, half = warp >> 1;
#pragma unroll
        for (int nt = 0; nt < 3; ++nt) {
            int ntile = half * 3 + nt;
            if (ntile >= 5) break;
            float c[4] = {0.f, 0.f, 0.f, 0.f};
#pragma unroll
            for (int kk = 0; kk < 8; ++kk) {
                uint32_t a[4], b2[2];
                int r = mt * 16 + (lane & 7) + ((lane >> 3) & 1) * 8;
                ldsm_x4(a, smem_u32(q_s + r * TA_LD + kk * 16 + (lane >> 4) * 8));
                ldsm_x2(b2, smem_u32(k_s + (ntile * 8 + (lane & 7)) * TA_LD + kk * 16 + ((lane >> 3) & 1) * 8));
                mma16816(c, a, b2);
            }
#pragma unroll
            for (int q = 0; q < 4; ++q) {
                int row = mt * 16 + g + (q >> 1) * 8, key = ntile * 8 + 2 * t4 + (q & 1);
                float v = bfr(bfr(c[q]) * scale);
                p_s[row * CH_LDP + key] = __float2bfloat16_rn(v);
            }
        }
    }
    __syncthreads();
    {
        int row = warp * 8 + (lane >> 2), l = lane & 3;
        float sc[10]; float mx = -3.0e38f;
#pragma unroll
        for (int q = 0; q < 10; ++q) {
            int key = l * 10 + q;
            float v = __bfloat162float(p_s[row * CH_LDP + key]);
            if (key > row + 8) v = -1.0e9f;
            sc[q] = v; mx = fmaxf(mx, v);
        }
        mx = fmaxf(mx, __shfl_xor_sync(0xffffffffu, mx, 1));
        mx = fmaxf(mx, __shfl_xor_sync(0xffffffffu, mx, 2));
        float sum = 0.f;
#pragma unroll
        for (int q = 0; q < 10; ++q) { sc[q] = expf(sc[q] - mx); sum += sc[q]; }
        sum += __shfl_xor_sync(0xffffffffu, sum, 1);
        sum += __shfl_xor_sync(0xffffffffu, sum, 2);
        float inv = 1.f / sum;
#pragma unroll
        for (int q = 0; q < 10; ++q) p_s[row * CH_LDP + l * 10 + q] = __float2bfloat16_rn(sc[q] * inv);
        if (l == 0) {
#pragma unroll
            for (int q = 40; q < 48; ++q) p_s[row * CH_LDP + q] = __float2bfloat16(0.f);
        }
    }
    __syncthreads();
    {
        int mt = warp & 1, eh = warp >> 1;
        uint32_t a[3][4];
#pragma unroll
        for (int kk = 0; kk < 3; ++kk) {
            int r = mt * 16 + (lane & 7) + ((lane >> 3) & 1) * 8;
            ldsm_x4(a[kk], smem_u32(p_s + r * CH_LDP + kk * 16 + (lane >> 4) * 8));
        }
#pragma unroll
        for (int nt = 0; nt < 8; nt += 2) {
            float c0[4] = {0.f,0.f,0.f,0.f}, c1[4] = {0.f,0.f,0.f,0.f};
#pragma unroll
            for (int kk = 0; kk < 3; ++kk) {
                uint32_t t[4];
                int r = kk * 16 + (lane & 7) + ((lane >> 3) & 1) * 8;
                ldsm_x4_t(t, smem_u32(v_s + r * TA_LD + eh * 64 + nt * 8 + (lane >> 4) * 8));
                mma16816(c0, a[kk], t);
                mma16816(c1, a[kk], t + 2);
            }
            int row = seg * SEG + mt * 16 + g;
            int col = h * DH + eh * 64 + nt * 8 + 2 * t4;
            *reinterpret_cast<uint32_t*>(g_o + (size_t)row * HD + col) = pack_bf16(c0[0], c0[1]);
            *reinterpret_cast<uint32_t*>(g_o + (size_t)(row + 8) * HD + col) = pack_bf16(c0[2], c0[3]);
            *reinterpret_cast<uint32_t*>(g_o + (size_t)row * HD + col + 8) = pack_bf16(c1[0], c1[1]);
            *reinterpret_cast<uint32_t*>(g_o + (size_t)(row + 8) * HD + col + 8) = pack_bf16(c1[2], c1[3]);
        }
    }
}

template <int BM, int BN, int WARPS_M, int WARPS_N, int STAGES, class P>
static void launch_gemm(const P& p, int M, cudaStream_t st) {
    constexpr int smem = STAGES * (BM * (32 + 8) + 32 * (BN + 8)) * 2;
    auto kern = gemm_kernel<BM, BN, WARPS_M, WARPS_N, STAGES, P>;
    cudaFuncSetAttribute(kern, cudaFuncAttributeMaxDynamicSharedMemorySize, smem);
    dim3 grid(M / BM, (p.N + BN - 1) / BN);
    kern<<<grid, WARPS_M * WARPS_N * 32, smem, st>>>(p);
}

typedef CUresult (*PFN_tmEncode)(CUtensorMap*, CUtensorMapDataType, cuuint32_t, void*, const cuuint64_t*, const cuuint64_t*,
                                 const cuuint32_t*, const cuuint32_t*, CUtensorMapInterleave, CUtensorMapSwizzle,
                                 CUtensorMapL2promotion, CUtensorMapFloatOOBfill);
static CUtensorMap make_map(PFN_tmEncode enc, const void* base, int rows, int cols, int box_rows) {
    CUtensorMap m;
    cuuint64_t dims[2] = {(cuuint64_t)cols, (cuuint64_t)rows};
    cuuint64_t strides[1] = {(cuuint64_t)cols * 2};
    cuuint32_t box[2] = {64, (cuuint32_t)box_rows};
    cuuint32_t es[2] = {1, 1};
    enc(&m, CU_TENSOR_MAP_DATA_TYPE_BFLOAT16, 2, const_cast<void*>(base), dims, strides, box, es,
        CU_TENSOR_MAP_INTERLEAVE_NONE, CU_TENSOR_MAP_SWIZZLE_128B, CU_TENSOR_MAP_L2_PROMOTION_L2_128B, CU_TENSOR_MAP_FLOAT_OOB_FILL_NONE);
    return m;
}
template <class P>
static void launch_wgemm(const P& p, const CUtensorMap& a, const CUtensorMap& b0, const CUtensorMap& b1, const CUtensorMap& b2, cudaStream_t st) {
    const int smem = WG_STAGES * 32768 + 1024;
    cudaFuncSetAttribute(wgemm_kernel<P>, cudaFuncAttributeMaxDynamicSharedMemorySize, smem);
    dim3 grid(S_LEN / 128, (p.N + 127) / 128);
    wgemm_kernel<P><<<grid, 288, smem, st>>>(a, b0, b1, b2, p);
}
template <class T> static void* sym_addr(T& sym) { void* a = nullptr; cudaGetSymbolAddress(&a, sym); return a; }

extern "C" void kernel_launch(void* const* d_in, const int* in_sizes, int n_in, void* d_out, int out_size) {
    const bf16* x     = (const bf16*)d_in[0];
    const bf16* mem0  = (const bf16*)d_in[1];
    const bf16* Wq    = (const bf16*)d_in[2];
    const bf16* Wk    = (const bf16*)d_in[3];
    const bf16* Wv    = (const bf16*)d_in[4];
    const bf16* Wo    = (const bf16*)d_in[5];
    const bf16* w1    = (const bf16*)d_in[8];
    const bf16* w2    = (const bf16*)d_in[9];
    const bf16* w3    = (const bf16*)d_in[10];
    const bf16* w4    = (const bf16*)d_in[11];
    const bf16* cvec  = (const bf16*)d_in[12];
    const bf16* w_mod = (const bf16*)d_in[13];
    bf16* out = (bf16*)d_out;
    cudaStream_t st = cudaStreamPerThread;

    mod_kernel<<<(6*DM)/64, 256, 0, st>>>(cvec, w_mod);
    ln1_kernel<<<S_LEN / 8, 256, 0, st>>>(x);
    void* fn = nullptr; cudaDriverEntryPointQueryResult qr;
    cudaGetDriverEntryPoint("cuTensorMapEncodeTiled", &fn, cudaEnableDefault, &qr);
    PFN_tmEncode enc = (PFN_tmEncode)fn;
    CUtensorMap a_h1 = make_map(enc, sym_addr(g_h1), S_LEN, DM, 128), a_o = make_map(enc, sym_addr(g_o), S_LEN, HD, 128);
    CUtensorMap a_a1 = make_map(enc, sym_addr(g_a1), S_LEN, DM, 128), a_g = make_map(enc, sym_addr(g_g), S_LEN, DM, 128);
    CUtensorMap a_a3 = make_map(enc, sym_addr(g_a3), S_LEN, DM, 128), a_u = make_map(enc, sym_addr(g_u), S_LEN, FF, 128);
    CUtensorMap b_q = make_map(enc, Wq, DM, HD, 64), b_k = make_map(enc, Wk, DM, HD, 64), b_v = make_map(enc, Wv, DM, HD, 64);
    CUtensorMap b_o = make_map(enc, Wo, HD, DM, 64), b_1 = make_map(enc, w1, DM, DM, 64), b_2 = make_map(enc, w2, DM, DM, 64);
    CUtensorMap b_3 = make_map(enc, w3, DM, FF, 64), b_4 = make_map(enc, w4, FF, DM, 64);
    { PQKV p{Wq, Wk, Wv, 3*HD, DM}; launch_wgemm(p, a_h1, b_q, b_k, b_v, st); }
    cudaFuncSetAttribute(chain_kernel, cudaFuncAttributeMaxDynamicSharedMemorySize, (int)sizeof(ChainSmem));
    chain_kernel<<<2*NH, 256, sizeof(ChainSmem), st>>>(mem0, Wq, Wk, Wv, Wo);
    tok_attn_kernel<<<NSEG * NH, 128, 0, st>>>();
    { POut p{Wo, x, DM, HD}; launch_wgemm(p, a_o, b_o, b_o, b_o, st); }
    ln2_kernel<<<S_LEN / 8, 256, 0, st>>>();
    { PW1 p{w1, DM, DM}; launch_wgemm(p, a_a1, b_1, b_1, b_1, st); }
    { PW2 p{w2, DM, DM}; launch_wgemm(p, a_g, b_2, b_2, b_2, st); }
    ln3_kernel<<<S_LEN / 8, 256, 0, st>>>();
    { PW3 p{w3, FF, DM}; launch_wgemm(p, a_a3, b_3, b_3, b_3, st); }
    { PW4 p{w4, out, DM, FF}; launch_wgemm(p, a_u, b_4, b_4, b_4, st); }
}
```
